```python
import torch

def _softmax(x, axis=-1):
    return torch.softmax(x, dim=axis)

def _gelu(x):
    return torch.nn.functional.gelu(x, approximate='tanh')

def _silu(x):
    return torch.nn.functional.silu(x)

def _sigmoid(x):
    return torch.sigmoid(x)

def _layernorm(x, axis=-1, eps=1e-05):
    m = x.mean(dim=axis, keepdim=True)
    v = x.var(dim=axis, keepdim=True, unbiased=False)
    return (x - m) / torch.sqrt(v + eps)

def _scatter_add(tgt, idx, src, axis=0):
    return tgt.clone().index_add_(axis, idx, src)

def _segment_sum(src, seg, n):
    out = torch.zeros((n,) + src.shape[1:], dtype=src.dtype)
    return out.index_add_(0, seg, src)

def _pad(x, pw):
    flat = tuple((v for pair in reversed(pw) for v in pair))
    return torch.nn.functional.pad(x, flat)
kernel_name = 'standalone__detection_seg_detr_decoder__vision'

def setup_inputs():

    _w = lambda a: (lambda t: t.to(torch.bfloat16) if t.is_floating_point() else t)(torch.as_tensor(a))
    H = W = 384 // 2 * 2
    C = 384
    Nq = 32
    return {'q': _w((lambda *s: torch.randn(*s, dtype=torch.bfloat16) * 0.05)(1, Nq, C)), 'feat_hi': _w((lambda *s: torch.randn(*s, dtype=torch.bfloat16) * 0.1)(1, H, W, C)), 'feat_lo': _w((lambda *s: torch.randn(*s, dtype=torch.bfloat16) * 0.1)(1, H // 2, W // 2, C)), 'lat_hi': _w((lambda *s: torch.randn(*s, dtype=torch.bfloat16) * 0.1)(C, C)), 'lat_lo': _w((lambda *s: torch.randn(*s, dtype=torch.bfloat16) * 0.1)(C, C)), 'wq': _w((lambda *s: torch.randn(*s, dtype=torch.bfloat16) * 0.1)(C, C)), 'wkv': _w((lambda *s: torch.randn(*s, dtype=torch.bfloat16) * 0.1)(C, 2 * C)), 'wo': _w((lambda *s: torch.randn(*s, dtype=torch.bfloat16) * 0.05)(C, C)), 'w1': _w((lambda *s: torch.randn(*s, dtype=torch.bfloat16) * 0.05)(C, 4 * C)), 'w2': _w((lambda *s: torch.randn(*s, dtype=torch.bfloat16) * 0.05)(4 * C, C))}

def reference(q, feat_hi, feat_lo, lat_hi, lat_lo, wq, wkv, wo, w1, w2):
    B, Nq, C = q.shape
    _, H, W, _ = feat_hi.shape
    lo = feat_lo @ lat_lo
    up = (lambda x, n, axis: torch.repeat_interleave(x, n, dim=axis))((lambda x, n, axis: torch.repeat_interleave(x, n, dim=axis))(lo, 2, axis=1), 2, axis=2)
    fused = feat_hi @ lat_hi + up
    mem = fused.reshape(B, H * W, C)
    qn = _layernorm(q, axis=-1)
    Q = qn @ wq
    KV = mem @ wkv
    K, V = (KV[..., :C].clone(), KV[..., C:].clone())
    scale = C ** (-0.5)
    logits = torch.einsum('bqc,bkc->bqk', Q, K) * scale
    P = _softmax(logits, axis=-1)
    O = torch.einsum('bqk,bkc->bqc', P, V)
    h = q + O @ wo
    hn = _layernorm(h, axis=-1)
    return h + _gelu(hn @ w1) @ w2
```

```cpp
#include <cuda_runtime.h>
#include <cuda_bf16.h>
#include <cuda.h>
#include <stdint.h>

namespace {
typedef __nv_bfloat16 bf16;
constexpr int C = 384, FF = 1536;
constexpr int NCTA = 128, NU = 1152;
constexpr int NG = 7, GB = 24576;
constexpr int NPRO = 24;
#define PACE 1
#define PFG 2
#define NSTAT 3
#define CLAIM_J 3
#define STATIC 0
constexpr uint32_t SM_Q = 0, SM_RING = 49152, SM_P = SM_RING + NG * GB, SM_PD = SM_P + 8192,
                   SM_WMAX = SM_PD + 2048, SM_ALPHA = SM_WMAX + 512, SM_BAR = SM_ALPHA + 256,
                   SM_TOTAL = SM_BAR + 256;
static_assert(SM_TOTAL <= 232448, "smem");
constexpr uint32_t B_FULL = SM_BAR, B_EMPTY = B_FULL + 8 * NG, B_PFULL = B_EMPTY + 8 * NG,
                   B_PEMPTY = B_PFULL + 16, B_Q = B_PEMPTY + 16, B_Z = B_Q + 8, S_MORE = B_Z + 8;
constexpr uint32_t SPIN_LIMIT = 1u << 22;

__device__ uint32_t g_epoch;
__device__ uint32_t g_cntW[2 * 32];
__device__ uint32_t g_gate, g_next;
__device__ __align__(128) uint32_t g_flagP[32];
__device__ uint4 g_act[2][4 * 1536];
__device__ __align__(16) uint32_t g_WvoT[C * C / 2];
__device__ uint4 g_WcF[16 * 72 * 32];
__device__ uint4 g_U[NCTA * 128 * 26];
constexpr int X_HP = 0, X_H = 16 * 32 * C, X_HN = X_H + 32 * C, X_A = X_HN + 32 * C / 2, X_END = X_A + 32 * FF / 2;
__device__ __align__(16) uint32_t g_x[X_END];
#define TS(i)

struct Params { const bf16 *q, *fhi, *flo, *lat_hi, *lat_lo, *wkv, *wo, *w1, *w2; bf16* out; };

__device__ __forceinline__ void mbar_init(uint32_t b, uint32_t n) { asm volatile("mbarrier.init.shared::cta.b64 [%0], %1;" ::"r"(b), "r"(n) : "memory"); }
__device__ __forceinline__ void mbar_arrive(uint32_t b) { asm volatile("mbarrier.arrive.shared::cta.b64 _, [%0];" ::"r"(b) : "memory"); }
__device__ __forceinline__ void mbar_expect(uint32_t b, uint32_t n) { asm volatile("mbarrier.arrive.expect_tx.shared::cta.b64 _, [%0], %1;" ::"r"(b), "r"(n) : "memory"); }
__device__ __forceinline__ void mbar_wait(uint32_t b, uint32_t par) {
    uint32_t ok, n = 0;
    do {
        asm volatile("{\n.reg .pred p;\nmbarrier.try_wait.parity.shared::cta.b64 p, [%1], %2;\nselp.u32 %0, 1, 0, p;\n}"
                     : "=r"(ok) : "r"(b), "r"(par) : "memory");
        if (++n > SPIN_LIMIT) __trap();
    } while (!ok);
}
__device__ __forceinline__ bool mbar_test(uint32_t b, uint32_t par) {
    uint32_t ok;
    asm volatile("{\n.reg .pred p;\nmbarrier.test_wait.parity.shared::cta.b64 p, [%1], %2;\nselp.u32 %0, 1, 0, p;\n}"
                 : "=r"(ok) : "r"(b), "r"(par) : "memory");
    return ok;
}
__device__ __forceinline__ void bar_sync(int id, int n) { asm volatile("bar.sync %0, %1;" ::"r"(id), "r"(n) : "memory"); }
__device__ __forceinline__ void fence_async() { asm volatile("fence.proxy.async;" ::: "memory"); }
__device__ __forceinline__ void fence_async_s() { asm volatile("fence.proxy.async.shared::cta;" ::: "memory"); }
__device__ __forceinline__ void fence_gpu() { asm volatile("fence.acq_rel.gpu;" ::: "memory"); }
__device__ __forceinline__ uint32_t ld_acq(const uint32_t* p) { uint32_t v; asm volatile("ld.acquire.gpu.global.u32 %0, [%1];" : "=r"(v) : "l"(p) : "memory"); return v; }
__device__ __forceinline__ uint32_t ld_rlx(const uint32_t* p) { uint32_t v; asm volatile("ld.relaxed.gpu.global.u32 %0, [%1];" : "=r"(v) : "l"(p) : "memory"); return v; }
__device__ __forceinline__ void st_rlx(uint32_t* p, uint32_t v) { asm volatile("st.relaxed.gpu.global.u32 [%0], %1;" ::"l"(p), "r"(v) : "memory"); }
__device__ __forceinline__ void poll_ge(const uint32_t* p, uint32_t tgt) {
    uint32_t n = 0;
    while ((int)(ld_acq(p) - tgt) < 0) { if (++n > SPIN_LIMIT) __trap(); }
}
__device__ __forceinline__ uint4 ld_rlx4(const void* p) {
    uint4 v; asm volatile("ld.relaxed.gpu.global.v4.u32 {%0, %1, %2, %3}, [%4];" : "=r"(v.x), "=r"(v.y), "=r"(v.z), "=r"(v.w) : "l"(p) : "memory");
    return v;
}
__device__ __forceinline__ bool nz4(const uint4& v) { return v.x && v.y && v.z && v.w; }
__device__ __forceinline__ uint4 poll4(const void* p) {
    uint4 v = ld_rlx4(p); uint32_t n = 0;
    while (!nz4(v)) { v = ld_rlx4(p); if (++n > SPIN_LIMIT) __trap(); }
    return v;
}
template <int N, int NT>
__device__ __forceinline__ void fetch_img(uint8_t* dst, const uint4* src, int i0) {
    uint4 v[N]; uint32_t n = 0; bool ok;
    do {
        ok = true;
#pragma unroll
        for (int i = 0; i < N; i++) v[i] = ld_rlx4(src + i0 + i * NT);
#pragma unroll
        for (int i = 0; i < N; i++) ok = ok && nz4(v[i]);
        if (++n > SPIN_LIMIT) __trap();
    } while (!ok);
#pragma unroll
    for (int i = 0; i < N; i++) reinterpret_cast<uint4*>(dst)[i0 + i * NT] = make_uint4(~v[i].x, ~v[i].y, ~v[i].z, ~v[i].w);
    fence_async_s();
}
__device__ __forceinline__ void gate_img(int f0, int nblk, int lane, uint32_t first, uint32_t tag) {
    if (lane >= f0 && lane < f0 + nblk) { uint32_t n = 0; while (first != tag) { first = ld_rlx(&g_flagP[lane]); if (++n > SPIN_LIMIT) __trap(); } }
    __syncwarp();
}
__device__ __forceinline__ bool more_units(uint32_t sb, int k) {
    uint32_t v, n = 0;
    do {
        asm volatile("ld.volatile.shared.u32 %0, [%1];" : "=r"(v) : "r"(sb + S_MORE + 4 * (k & 3)) : "memory");
        if (++n > SPIN_LIMIT) __trap();
    } while ((int)(v >> 1) != k + 1);
    return v & 1;
}
__device__ __forceinline__ uint32_t pack2(float lo, float hi) { uint32_t r; asm("cvt.rn.bf16x2.f32 %0, %1, %2;" : "=r"(r) : "f"(hi), "f"(lo)); return r; }
__device__ __forceinline__ float bflo(uint32_t v) { return __uint_as_float(v << 16); }
__device__ __forceinline__ float bfhi(uint32_t v) { return __uint_as_float(v & 0xffff0000u); }
__device__ __forceinline__ float ex2(float x) { float r; asm("ex2.approx.ftz.f32 %0, %1;" : "=f"(r) : "f"(x)); return r; }
__device__ __forceinline__ uint32_t movtrans(uint32_t v) { uint32_t r; asm volatile("movmatrix.sync.aligned.m8n8.trans.b16 %0, %1;" : "=r"(r) : "r"(v)); return r; }
__device__ __forceinline__ void stsm4t(uint32_t a, uint32_t r0, uint32_t r1, uint32_t r2, uint32_t r3) {
    asm volatile("stmatrix.sync.aligned.m8n8.x4.trans.shared.b16 [%0], {%1, %2, %3, %4};" ::"r"(a), "r"(r0), "r"(r1), "r"(r2), "r"(r3) : "memory");
}
__device__ __forceinline__ uint4 ldsm4t(uint32_t a) {
    uint4 r; asm volatile("ldmatrix.sync.aligned.m8n8.x4.trans.shared.b16 {%0, %1, %2, %3}, [%4];" : "=r"(r.x), "=r"(r.y), "=r"(r.z), "=r"(r.w) : "r"(a) : "memory");
    return r;
}
__device__ __forceinline__ void mma16816(float (&d)[4], const uint32_t a0, const uint32_t a1, const uint32_t a2, const uint32_t a3, uint32_t b0, uint32_t b1) {
    asm volatile("mma.sync.aligned.m16n8k16.row.col.f32.bf16.bf16.f32 {%0,%1,%2,%3}, {%4,%5,%6,%7}, {%8,%9}, {%0,%1,%2,%3};"
                 : "+f"(d[0]), "+f"(d[1]), "+f"(d[2]), "+f"(d[3]) : "r"(a0), "r"(a1), "r"(a2), "r"(a3), "r"(b0), "r"(b1));
}
__device__ __forceinline__ uint32_t dlA(uint32_t a) { return (a >> 4) | (64u << 16); }
__device__ __forceinline__ uint32_t dlB(uint32_t a) { return (a >> 4) | (32u << 16); }
template <int TA, int SBO, int OA, int OB, int SC>
__device__ __forceinline__ void wgmma32(float (&d)[16], uint32_t la, uint32_t lb) {
    asm volatile("{\n.reg .pred p;\n.reg .b32 x, y;\n.reg .b64 da, db;\nsetp.ne.b32 p, %18, 0;\n"
                 "add.u32 x, %16, %20;\nadd.u32 y, %17, %21;\nmov.b64 da, {x, %22};\nmov.b64 db, {y, 8};\n"
                 "wgmma.mma_async.sync.aligned.m64n32k16.f32.bf16.bf16 "
                 "{%0,%1,%2,%3,%4,%5,%6,%7,%8,%9,%10,%11,%12,%13,%14,%15}, da, db, p, 1, 1, %19, 0;\n}"
                 : "+f"(d[0]), "+f"(d[1]), "+f"(d[2]), "+f"(d[3]), "+f"(d[4]), "+f"(d[5]), "+f"(d[6]), "+f"(d[7]),
                   "+f"(d[8]), "+f"(d[9]), "+f"(d[10]), "+f"(d[11]), "+f"(d[12]), "+f"(d[13]), "+f"(d[14]), "+f"(d[15])
                 : "r"(la), "r"(lb), "n"(SC), "n"(TA), "n"(OA >> 4), "n"(OB >> 4), "n"((SBO >> 4) | 0x40000000));
}
template <int TA, int SBO, int N, int PER, int CH, int ST, int OA, int OB, int SC0, int I = 0>
__device__ __forceinline__ void wgchain(float (&d)[16], uint32_t la, uint32_t lb) {
    if constexpr (I < N) {
        wgmma32<TA, SBO, OA + (I / PER) * CH + (I % PER) * ST, OB + I * 1024, (I == 0 ? SC0 : 1)>(d, la, lb);
        wgchain<TA, SBO, N, PER, CH, ST, OA, OB, SC0, I + 1>(d, la, lb);
    }
}
template <int TA, int SBO, int N, int PER, int CH, int ST, int OA, int OB, int SC0, int I = 0>
__device__ __forceinline__ void wgchain2(float (&d)[16], float (&e)[16], uint32_t la, uint32_t lb) {
    if constexpr (I < N) {
        wgmma32<TA, SBO, OA + (I / PER) * CH + (I % PER) * ST, OB + I * 1024, (I < 2 ? SC0 : 1)>(d, la, lb);
        wgchain2<TA, SBO, N, PER, CH, ST, OA, OB, SC0, I + 1>(e, d, la, lb);
    }
}
template <int N, int CH, int OB, int I = 0>
__device__ __forceinline__ void wgpv(float (&a)[16], float (&b)[16], float (&c)[16], uint32_t la, uint32_t lb) {
    if constexpr (I < N) {
        wgmma32<1, 1024, I * 2048, OB + I * 1024, 1>(a, la, lb);
        wgmma32<1, 1024, CH + I * 2048, OB + I * 1024, 1>(b, la, lb);
        wgmma32<1, 1024, 2 * CH + I * 2048, OB + I * 1024, 1>(c, la, lb);
        wgpv<N, CH, OB, I + 1>(a, b, c, la, lb);
    }
}
__device__ __forceinline__ void wg_fence() { asm volatile("wgmma.fence.sync.aligned;" ::: "memory"); }
__device__ __forceinline__ void wg_commit() { asm volatile("wgmma.commit_group.sync.aligned;" ::: "memory"); }
__device__ __forceinline__ void wg_wait0() { asm volatile("wgmma.wait_group.sync.aligned 0;" ::: "memory"); }
__device__ __forceinline__ void pin(float (&d)[16]) {
#pragma unroll
    for (int i = 0; i < 16; i++) asm volatile("" : "+f"(d[i])::"memory");
}
__device__ __forceinline__ void tma2(uint32_t dst, const CUtensorMap* m, int c0, int c1, uint32_t bar) {
    asm volatile("cp.async.bulk.tensor.2d.shared::cluster.global.mbarrier::complete_tx::bytes [%0], [%1, {%3, %4}], [%2];"
                 ::"r"(dst), "l"(m), "r"(bar), "r"(c0), "r"(c1) : "memory");
}
__device__ __forceinline__ void tma3(uint32_t dst, const CUtensorMap* m, int c1, int c2, uint32_t bar, uint64_t pol) {
    asm volatile("cp.async.bulk.tensor.3d.shared::cluster.global.mbarrier::complete_tx::bytes.L2::cache_hint [%0], [%1, {%3, %4, %5}], [%2], %6;"
                 ::"r"(dst), "l"(m), "r"(bar), "r"(0), "r"(c1), "r"(c2), "l"(pol) : "memory");
}
__device__ __forceinline__ void tma5(uint32_t dst, const CUtensorMap* m, int c3, int c4, uint32_t bar, uint64_t pol) {
    asm volatile("cp.async.bulk.tensor.5d.shared::cluster.global.mbarrier::complete_tx::bytes.L2::cache_hint [%0], [%1, {%3, %3, %3, %4, %5}], [%2], %6;"
                 ::"r"(dst), "l"(m), "r"(bar), "r"(0), "r"(c3), "r"(c4), "l"(pol) : "memory");
}
__device__ __forceinline__ void bulk_g2s(uint32_t dst, const void* src, uint32_t n, uint32_t bar) {
    asm volatile("cp.async.bulk.shared::cluster.global.mbarrier::complete_tx::bytes [%0], [%1], %2, [%3];" ::"r"(dst), "l"(src), "r"(n), "r"(bar) : "memory");
}
__device__ __forceinline__ void l2_prefetch(const void* src, uint32_t n) { asm volatile("cp.async.bulk.prefetch.L2.global [%0], %1;" ::"l"(src), "r"(n) : "memory"); }
__device__ __forceinline__ float wsum(float v) {
#pragma unroll
    for (int o = 16; o; o >>= 1) v += __shfl_xor_sync(~0u, v, o);
    return v;
}

__device__ __forceinline__ void tail(const Params& p, uint32_t tag, uint8_t* sm, uint32_t sb, int slot, int ph) {
    const int tid = threadIdx.x - 128, wid = tid >> 5, lane = tid & 31, g = lane >> 2, t = lane & 3, cta = blockIdx.x;
    const int rg = cta >> 4, cs = cta & 15;
    float* red = reinterpret_cast<float*>(sm + SM_RING + (slot ? slot - 1 : NG - 1) * GB);
    float4* redW = reinterpret_cast<float4*>(red + 3072);
    float4* redM = redW + 128;
    bf16* Us = reinterpret_cast<bf16*>(redM + 8);
    float* rs = reinterpret_cast<float*>(Us + 8 * 56);
    float* red2 = reinterpret_cast<float*>(sm + SM_Q + 1024);
    auto frag = [&](int gi) -> const uint4* {
        const int sl = slot + gi >= NG ? slot + gi - NG : slot + gi;
        mbar_wait(sb + B_FULL + 8 * sl, slot + gi >= NG ? ph ^ 1 : ph);
        return reinterpret_cast<const uint4*>(sm + SM_RING + sl * GB);
    };
    if (tid == 0) { poll_ge(&g_gate, tag * NCTA); TS(6); }
    bar_sync(2, 384);
    {
        const int pg = tid / 24, u = tid - pg * 24;
        const uint4* src = &g_U[(pg * 128 + cta) * 26] + u;
        const uint32_t par = tag & 1;
        uint4 v[8]; uint32_t n = 0;
#pragma unroll
        for (int i = 0; i < 8; i++) v[i] = ld_rlx4(src + i * (16 * 128 * 26));
#define FM(x) __uint_as_float((x) & ~1u)
#define BAD4(v) ((((v).x ^ par) | ((v).y ^ par) | ((v).z ^ par) | ((v).w ^ par)) & 1)
        float4 mm, ll;
        if (tid < 128) {
            const uint4* ml = &g_U[(tid * 128 + cta) * 26 + 24];
            uint4 m, l;
            do { m = ld_rlx4(ml); l = ld_rlx4(ml + 1); if (++n > SPIN_LIMIT) __trap(); } while (BAD4(m) | BAD4(l));
            mm = make_float4(FM(m.x), FM(m.y), FM(m.z), FM(m.w)); ll = make_float4(FM(l.x), FM(l.y), FM(l.z), FM(l.w));
            float4 M = mm;
#pragma unroll
            for (int o = 16; o; o >>= 1) {
                M.x = fmaxf(M.x, __shfl_xor_sync(~0u, M.x, o)); M.y = fmaxf(M.y, __shfl_xor_sync(~0u, M.y, o));
                M.z = fmaxf(M.z, __shfl_xor_sync(~0u, M.z, o)); M.w = fmaxf(M.w, __shfl_xor_sync(~0u, M.w, o));
            }
            if (lane == 0) redM[wid] = M;
            bar_sync(1, 128);
            const float4 a = redM[0], b = redM[1], c = redM[2], d = redM[3];
            const float4 w4 = make_float4(ex2(mm.x - fmaxf(fmaxf(a.x, b.x), fmaxf(c.x, d.x))), ex2(mm.y - fmaxf(fmaxf(a.y, b.y), fmaxf(c.y, d.y))),
                                          ex2(mm.z - fmaxf(fmaxf(a.z, b.z), fmaxf(c.z, d.z))), ex2(mm.w - fmaxf(fmaxf(a.w, b.w), fmaxf(c.w, d.w))));
            redW[tid] = w4;
            const float4 L = make_float4(wsum(w4.x * ll.x), wsum(w4.y * ll.y), wsum(w4.z * ll.z), wsum(w4.w * ll.w));
            if (lane == 0) redM[4 + wid] = L;
        }
#pragma unroll
        for (int i = 0; i < 8; i++)
            while (((v[i].x ^ par) | (v[i].z ^ par)) & 1) { v[i] = ld_rlx4(src + i * (16 * 128 * 26)); if (++n > SPIN_LIMIT) __trap(); }
        bar_sync(2, 384);
        if (tid == 0) TS(12);
        float a[8] = {0, 0, 0, 0, 0, 0, 0, 0};
#pragma unroll
        for (int i = 0; i < 8; i++) {
            const float4 w = redW[pg + 16 * i];
            a[0] += w.x * bflo(v[i].x & ~1u); a[1] += w.y * bfhi(v[i].x); a[2] += w.x * bflo(v[i].y); a[3] += w.y * bfhi(v[i].y);
            a[4] += w.z * bflo(v[i].z & ~1u); a[5] += w.w * bfhi(v[i].z); a[6] += w.z * bflo(v[i].w); a[7] += w.w * bfhi(v[i].w);
        }
        float4* dst = reinterpret_cast<float4*>(red + pg * 192 + u * 8);
        dst[0] = make_float4(a[0], a[1], a[2], a[3]); dst[1] = make_float4(a[4], a[5], a[6], a[7]);
        if (tid < 112) reinterpret_cast<uint32_t*>(Us + 4 * 56)[tid] = 0;
        const uint4* wcp = frag(wid >= 8) + (wid & 7) * 192 + lane;
        uint4 wc[6];
#pragma unroll
        for (int i = 0; i < 6; i++) wc[i] = wcp[32 * i];
        bar_sync(2, 384);
        if (tid < 192) {
            const int j = tid & 7, uu = tid >> 3, ql = 2 * (j >> 2) + (j & 1), ch = 16 * (uu >> 3) + (uu & 7) + 8 * ((j >> 1) & 1);
            const float* pl = reinterpret_cast<const float*>(redM + 4) + ql;
            float num = 0;
#pragma unroll
            for (int i = 0; i < 16; i++) num += red[i * 192 + tid];
            Us[ql * 56 + ch] = __float2bfloat16(__fdividef(num, (pl[0] + pl[4]) + (pl[8] + pl[12])));
        }
        bar_sync(2, 384);
        const uint32_t* ub = reinterpret_cast<const uint32_t*>(Us + g * 56) + t;
#pragma unroll
        for (int j = 0; j < 2; j++) {
            float d[4] = {0, 0, 0, 0};
#pragma unroll
            for (int ks = 0; ks < 3; ks++) mma16816(d, wc[3 * j + ks].x, wc[3 * j + ks].y, wc[3 * j + ks].z, wc[3 * j + ks].w, ub[8 * ks], ub[8 * ks + 4]);
            if (t < 2) {
                uint32_t* o = &g_x[X_HP + (cs * 32 + 4 * rg + 2 * t) * C + 16 * (2 * wid + j) + g];
                st_rlx(o, ~__float_as_uint(d[0])); st_rlx(o + C, ~__float_as_uint(d[1]));
                st_rlx(o + 8, ~__float_as_uint(d[2])); st_rlx(o + C + 8, ~__float_as_uint(d[3]));
            }
        }
        if (tid == 0) TS(7);
    }
    if (cta >= 96) {
        const int q = cta - 96;
        const float qv = __bfloat162float(p.q[q * C + tid]);
        uint32_t v[16], n = 0; bool ok;
        do {
            ok = true;
#pragma unroll
            for (int i = 0; i < 16; i++) v[i] = ld_rlx(&g_x[X_HP + (i * 32 + q) * C + tid]);
#pragma unroll
            for (int i = 0; i < 16; i++) ok = ok && v[i];
            if (++n > SPIN_LIMIT) __trap();
        } while (!ok);
        float h = qv;
#pragma unroll
        for (int i = 0; i < 16; i++) h += __uint_as_float(~v[i]);
        st_rlx(&g_x[X_H + q * C + tid], ~__float_as_uint(h));
        float s = wsum(h);
        if (lane == 0) rs[wid] = s;
        bar_sync(2, 384);
        s = 0;
#pragma unroll
        for (int i = 0; i < 12; i++) s += rs[i];
        const float dv = h - s * (1.0f / C);
        float s2 = wsum(dv * dv);
        if (lane == 0) rs[16 + wid] = s2;
        bar_sync(2, 384);
        s2 = 0;
#pragma unroll
        for (int i = 0; i < 12; i++) s2 += rs[16 + i];
        const float hn = dv * rsqrtf(s2 * (1.0f / C) + 1e-5f);
        const float hn1 = __shfl_down_sync(~0u, hn, 1);
        if (!(lane & 1)) st_rlx(&g_x[X_HN + q * (C / 2) + (tid >> 1)], ~pack2(hn, hn1));
        if (tid == 0) TS(8);
        return;
    }
    const int r4 = cta / 24, c24 = cta - r4 * 24;
    uint4 A1[8], A2[8];
    {
        const int kr = 8 * ((lane & 7) >> 1) + (lane & 1) + 2 * (lane >> 4), hi = (lane >> 3) & 1;
        const uint32_t f1 = (uint32_t)__cvta_generic_to_shared(frag(2 + (wid >= 6))) + (32 * (wid % 6) + kr) * 128;
        const uint32_t f2 = (uint32_t)__cvta_generic_to_shared(frag(4 + (wid >= 6))) + (128 * (wid % 6) + kr) * 32 + hi * 16;
#pragma unroll
        for (int s = 0; s < 8; s++) {
            A1[s] = ldsm4t(f1 + (s & 1) * 512 + (((2 * (s >> 1) + hi) ^ ((kr + 4 * (s & 1)) & 7)) << 4));
            A2[s] = ldsm4t(f2 + (32 * (s >> 1) + 4 * (s & 1)) * 32);
        }
    }
    {
        const uint4 b = poll4(&g_x[X_HN + (8 * r4 + g) * (C / 2) + 16 * wid + 4 * t]);
        __syncwarp();
        if (tid == 0) TS(8);
#pragma unroll
        for (int mt = 0; mt < 4; mt++) {
            float d[4] = {0, 0, 0, 0};
            mma16816(d, A1[2 * mt].x, A1[2 * mt].y, A1[2 * mt].z, A1[2 * mt].w, ~b.x, ~b.y);
            mma16816(d, A1[2 * mt + 1].x, A1[2 * mt + 1].y, A1[2 * mt + 1].z, A1[2 * mt + 1].w, ~b.z, ~b.w);
            float* o = red2 + (wid * 8 + 2 * t) * 68 + 16 * mt + g;
            o[0] = d[0]; o[68] = d[1]; o[8] = d[2]; o[76] = d[3];
        }
        bar_sync(2, 384);
        if (tid < 256) {
            const float2* r2 = reinterpret_cast<const float2*>(red2 + wid * 68) + lane;
            float x = 0, y = 0;
#pragma unroll
            for (int i = 0; i < 12; i++) { const float2 z = r2[i * 272]; x += z.x; y += z.y; }
            const float ex = __expf(-1.5957691216057308f * (x + 0.044715f * x * x * x)), ey = __expf(-1.5957691216057308f * (y + 0.044715f * y * y * y));
            st_rlx(&g_x[X_A + (8 * r4 + wid) * (FF / 2) + 32 * c24 + lane], ~pack2(x / (1.0f + ex), y / (1.0f + ey)));
        }
        if (tid == 0) TS(9);
    }
    {
        const int oq = 8 * r4 + (tid >> 3), oc = 16 * c24 + 2 * (tid & 7);
        const uint32_t* src = &g_x[X_A + (8 * r4 + g) * (FF / 2) + 64 * wid + 4 * t];
        uint4 b[4];
        b[0] = poll4(src);
#pragma unroll
        for (int j = 1; j < 4; j++) b[j] = ld_rlx4(src + 16 * j);
        uint32_t h0 = 1, h1 = 1;
        if (tid < 64) { h0 = ld_rlx(&g_x[X_H + oq * C + oc]); h1 = ld_rlx(&g_x[X_H + oq * C + oc + 1]); }
#pragma unroll
        for (int j = 1; j < 4; j++) if (!nz4(b[j])) b[j] = poll4(src + 16 * j);
        __syncwarp();
        if (tid == 0) TS(10);
        float d[4] = {0, 0, 0, 0}, e[4] = {0, 0, 0, 0};
#pragma unroll
        for (int j = 0; j < 4; j++) {
            mma16816(d, A2[2 * j].x, A2[2 * j].y, A2[2 * j].z, A2[2 * j].w, ~b[j].x, ~b[j].y);
            mma16816(e, A2[2 * j + 1].x, A2[2 * j + 1].y, A2[2 * j + 1].z, A2[2 * j + 1].w, ~b[j].z, ~b[j].w);
        }
        float* o = red + (wid * 8 + 2 * t) * 20 + g;
        o[0] = d[0] + e[0]; o[20] = d[1] + e[1]; o[8] = d[2] + e[2]; o[28] = d[3] + e[3];
        bar_sync(2, 384);
        if (tid < 64) {
            uint32_t n = 0;
            while (!h0 || !h1) { h0 = ld_rlx(&g_x[X_H + oq * C + oc]); h1 = ld_rlx(&g_x[X_H + oq * C + oc + 1]); if (++n > SPIN_LIMIT) __trap(); }
            float x = __uint_as_float(~h0), y = __uint_as_float(~h1);
            const float2* r = reinterpret_cast<const float2*>(red + (tid >> 3) * 20) + (tid & 7);
#pragma unroll
            for (int i = 0; i < 12; i++) { const float2 z = r[80 * i]; x += z.x; y += z.y; }
            *reinterpret_cast<uint32_t*>(p.out + oq * C + oc) = pack2(x, y);
        }
        if (tid == 0) { if (cta == 0) { st_rlx(&g_next, 0); st_rlx(&g_epoch, tag); } TS(11); }
    }
}

__device__ __forceinline__ void wcomb(const Params& p, uint32_t tag, int hw, int lane) {
    const int g = lane >> 2, t = lane & 3, mt = hw % 24, grp = hw / 24;
    {
        float d[4][4] = {};
        const bf16* wv = p.wkv + (size_t)(32 * grp + g) * (2 * C) + C + 8 * t;
        const uint32_t* wo = reinterpret_cast<const uint32_t*>(p.wo + (8 * (g >> 1) + (g & 1)) * C + 16 * mt) + t;
#pragma unroll 1
        for (int k3 = 0; k3 < 12; k3 += 3) {
            uint32_t a[3][8]; uint4 b[3][4];
#pragma unroll
            for (int kk = 0; kk < 3; kk++) {
#pragma unroll
                for (int i = 0; i < 8; i++) a[kk][i] = __ldg(wo + (32 * (k3 + kk) + 2 * (i >> 1)) * (C / 2) + 4 * (i & 1));
#pragma unroll
                for (int j = 0; j < 4; j++) b[kk][j] = __ldg(reinterpret_cast<const uint4*>(wv + (size_t)j * 8 * 2 * C + 32 * (k3 + kk)));
            }
#pragma unroll
            for (int kk = 0; kk < 3; kk++) {
#pragma unroll
                for (int i = 0; i < 8; i++) a[kk][i] = movtrans(a[kk][i]);
#pragma unroll
                for (int j = 0; j < 4; j++) {
                    mma16816(d[j], a[kk][0], a[kk][1], a[kk][2], a[kk][3], b[kk][j].x, b[kk][j].y);
                    mma16816(d[j], a[kk][4], a[kk][5], a[kk][6], a[kk][7], b[kk][j].z, b[kk][j].w);
                }
            }
        }
#pragma unroll
        for (int j = 0; j < 4; j++) {
            uint32_t* o = &g_WvoT[(16 * mt + g) * (C / 2) + 16 * grp + 4 * j + t];
            o[0] = pack2(d[j][0], d[j][1]); o[8 * (C / 2)] = pack2(d[j][2], d[j][3]);
        }
        __syncwarp();
        if (lane == 0) { fence_gpu(); atomicAdd(&g_cntW[0], 1u); poll_ge(&g_cntW[0], tag * 288u); TS(15); }
        __syncwarp();
    }
    {
        float d[8][4] = {};
        const bf16* lat = (grp < 6 ? p.lat_hi + (size_t)(64 * grp) * C : p.lat_lo + (size_t)(64 * (grp - 6)) * C) + g * C + 8 * t;
        const uint4* wa = reinterpret_cast<const uint4*>(g_WvoT) + (16 * mt + g) * 48 + t;
#pragma unroll 1
        for (int k2 = 0; k2 < 12; k2 += 2) {
            uint4 a[2][2], b[2][8];
#pragma unroll
            for (int kk = 0; kk < 2; kk++) {
                a[kk][0] = __ldcg(wa + 4 * (k2 + kk)); a[kk][1] = __ldcg(wa + 8 * 48 + 4 * (k2 + kk));
#pragma unroll
                for (int j = 0; j < 8; j++) b[kk][j] = __ldg(reinterpret_cast<const uint4*>(lat + j * 8 * C + 32 * (k2 + kk)));
            }
#pragma unroll
            for (int kk = 0; kk < 2; kk++)
#pragma unroll
                for (int j = 0; j < 8; j++) {
                    mma16816(d[j], a[kk][0].x, a[kk][1].x, a[kk][0].y, a[kk][1].y, b[kk][j].x, b[kk][j].y);
                    mma16816(d[j], a[kk][0].z, a[kk][1].z, a[kk][0].w, a[kk][1].w, b[kk][j].z, b[kk][j].w);
                }
        }
#pragma unroll
        for (int j = 0; j < 4; j++)
            g_WcF[(((4 * grp + j) / 3) * 72 + mt * 3 + (4 * grp + j) % 3) * 32 + lane] = make_uint4(pack2(d[2 * j][0], d[2 * j][1]), pack2(d[2 * j][2], d[2 * j][3]),
                                                                   pack2(d[2 * j + 1][0], d[2 * j + 1][1]), pack2(d[2 * j + 1][2], d[2 * j + 1][3]));
        __syncwarp();
        fence_async();
        __syncwarp();
        if (lane == 0) { fence_gpu(); atomicAdd(&g_cntW[32], 1u); TS(13); }
    }
}

__global__ void __launch_bounds__(512, 1)
detr_kernel(const __grid_constant__ CUtensorMap tmHi, const __grid_constant__ CUtensorMap tmLo,
            const __grid_constant__ CUtensorMap tmWq, const __grid_constant__ CUtensorMap tmWk,
            const __grid_constant__ CUtensorMap tmLh, const __grid_constant__ CUtensorMap tmLl,
            const __grid_constant__ CUtensorMap tmW1, const __grid_constant__ CUtensorMap tmW2, const Params p) {
    extern __shared__ __align__(1024) uint8_t sm[];
    const uint32_t sb = (uint32_t)__cvta_generic_to_shared(sm);
    const int tid = threadIdx.x, wid = tid >> 5, lane = tid & 31, cta = blockIdx.x;
    const int g = lane >> 2, t = lane & 3, w = wid & 3;
    const int pos0 = cta < NPRO ? 2 : 0;
    const uint32_t flag0 = wid == 4 ? ld_rlx(&g_flagP[lane]) : 0, epoch = ld_rlx(&g_epoch);
    int slot = pos0, ph = 0;
    if (tid == 0) {
        TS(0);
        if (sb & 1023) __trap();
        for (int i = 0; i < NG; i++) { mbar_init(sb + B_FULL + 8 * i, 1); mbar_init(sb + B_EMPTY + 8 * i, 8); }
        for (int i = 0; i < 2; i++) { mbar_init(sb + B_PFULL + 8 * i, 128); mbar_init(sb + B_PEMPTY + 8 * i, 8); }
        mbar_init(sb + B_Q, 384); mbar_init(sb + B_Z, 3);
        *reinterpret_cast<uint4*>(sm + S_MORE) = make_uint4(0, 0, 0, 0);
        asm volatile("fence.mbarrier_init.release.cluster;" ::: "memory");
        fence_async();
            if (cta < NPRO) {
                uint64_t poln; asm volatile("createpolicy.fractional.L2::evict_normal.b64 %0, 1.0;" : "=l"(poln));
                for (int h = 0; h < 2; h++) {
                    const uint32_t dst = sb + SM_RING + h * GB, bar = sb + B_FULL + 8 * h;
                    mbar_expect(bar, GB);
                    if (cta < 6) tma2(dst, &tmWq, 64 * cta, 192 * h, bar);
                    else if (cta < 12) tma3(dst, &tmWk, 64 * (cta - 6), 3 * h, bar, poln);
                    else if (cta < 18) tma3(dst, &tmLh, 64 * (cta - 12), 3 * h, bar, poln);
                    else tma3(dst, &tmLl, 64 * (cta - 18), 3 * h, bar, poln);
                }
            }
    }
    if (cta < 6 && (wid >> 2) == 1) {
        const int row = (tid & 127) >> 2;
        uint4 x[12];
#pragma unroll
        for (int j = 0; j < 12; j++) x[j] = __ldg(reinterpret_cast<const uint4*>(p.q + row * C) + 4 * j + t);
                float sum = 0;
#pragma unroll
                for (int j = 0; j < 12; j++) sum += ((bflo(x[j].x) + bfhi(x[j].x)) + (bflo(x[j].y) + bfhi(x[j].y))) + ((bflo(x[j].z) + bfhi(x[j].z)) + (bflo(x[j].w) + bfhi(x[j].w)));
                sum += __shfl_xor_sync(~0u, sum, 1); sum += __shfl_xor_sync(~0u, sum, 2);
                const float mean = sum * (1.0f / C);
                float var = 0;
#define SQ2(v) ((bflo(v) - mean) * (bflo(v) - mean) + (bfhi(v) - mean) * (bfhi(v) - mean))
#pragma unroll
                for (int j = 0; j < 12; j++) var += (SQ2(x[j].x) + SQ2(x[j].y)) + (SQ2(x[j].z) + SQ2(x[j].w));
                var += __shfl_xor_sync(~0u, var, 1); var += __shfl_xor_sync(~0u, var, 2);
                const float rstd = rsqrtf(var * (1.0f / C) + 1e-5f);
#define NRM(v) pack2((bflo(v) - mean) * rstd, (bfhi(v) - mean) * rstd)
#pragma unroll
                for (int j = 0; j < 12; j++)
                    *reinterpret_cast<uint4*>(sm + SM_Q + (4 * j + t) * 512 + row * 16) = make_uint4(NRM(x[j].x), NRM(x[j].y), NRM(x[j].z), NRM(x[j].w));
                fence_async_s();
    }
    __syncthreads();
    const uint32_t tag = epoch + 1;
    const uint4* act = g_act[tag & 1];

    if (wid < 4) {
        if (tid == 0) {
            uint64_t pol; asm volatile("createpolicy.fractional.L2::evict_first.b64 %0, 1.0;" : "=l"(pol));
            int cnt = pos0, U = cta, Un = NCTA + cta;
            ph = 1;
            for (int k = 0; U < NU; k++) {
                const int b0 = (U / 6) * 48 + 4 * (U % 6);
#pragma unroll 1
                for (int j = 0; j < 5; j++) {
                    if (cnt >= PACE && cnt < NG) mbar_wait(sb + B_FULL + 8 * (cnt - PACE), 0);
                    if (PFG && cnt == NG) {
                        const uint8_t* prev = nullptr;
                        for (int n = NG - pos0; n < NG - pos0 + PFG && n < 5 * NSTAT; n++) {
                            const int UU = (n / 5) * NCTA + cta, jj = n % 5, bb = (UU / 6) * 48 + 4 * (UU % 6);
                            const uint8_t* src = jj == 2 ? reinterpret_cast<const uint8_t*>(p.flo + (size_t)UU * 32 * C)
                                : reinterpret_cast<const uint8_t*>(p.fhi + (size_t)(bb + (jj > 2 ? 24 : 0)) * 16 * C) + ((jj == 1 || jj == 4) ? GB : 0);
                            if (!prev) mbar_wait(sb + B_FULL + 8 * (NG - PACE), 0);
                            if (mbar_test(sb + B_Q, 0)) break;
                            l2_prefetch(src, GB);
                            if (prev) { if (ld_rlx(reinterpret_cast<const uint32_t*>(prev + GB - 4)) == 0x9e3779b9u) __nanosleep(1); }
                            else mbar_wait(sb + B_FULL + 8 * (NG - 1), 0);
                            prev = src;
                        }
                    }
                    cnt++;
                    const uint32_t dst = sb + SM_RING + slot * GB, bar = sb + B_FULL + 8 * slot;
                    mbar_wait(sb + B_EMPTY + 8 * slot, ph);
                    if (j == CLAIM_J) Un = (STATIC || k < NSTAT - 1) ? U + NCTA : NSTAT * NCTA + (int)atomicAdd(&g_next, 1u);
                    mbar_expect(bar, GB);
                    if (j == 2) tma3(dst, &tmLo, 32 * U, 0, bar, pol);
                    else tma5(dst, &tmHi, b0 + (j > 2 ? 24 : 0), (j == 1 || j == 4) ? 3 : 0, bar, pol);
                    if (++slot == NG) { slot = 0; ph ^= 1; }
                }
                if (k == 5) {
                    l2_prefetch(reinterpret_cast<const uint8_t*>(p.w1) + cta * 9216, 9216);
                    l2_prefetch(reinterpret_cast<const uint8_t*>(p.w2) + cta * 9216, 9216);
                }
                U = Un;
                asm volatile("st.volatile.shared.u32 [%0], %1;" ::"r"(sb + S_MORE + 4 * (k & 3)), "r"(2 * (k + 1) + (U < NU)) : "memory");
            }
            poll_ge(&g_cntW[32], tag * 288u);
            fence_async();
            for (int j = 0; j < (cta < 96 ? 6 : 2); j++) {
                const uint32_t bytes = j == 1 ? GB / 2 : GB, bar = sb + B_FULL + 8 * slot;
                const uint32_t dst = sb + SM_RING + slot * GB;
                mbar_wait(sb + B_EMPTY + 8 * slot, ph);
                mbar_expect(bar, bytes);
                if (j < 2) bulk_g2s(dst, &g_WcF[(cta & 15) * 2304 + j * 1536], bytes, bar);
                else if (j < 4) tma2(dst, &tmW1, 64 * (cta % 24), 192 * (j - 2), bar);
                else for (int i = 0; i < 3; i++) tma2(dst + i * 8192, &tmW2, 16 * (cta % 24), 768 * (j - 4) + 256 * i, bar);
                if (++slot == NG) { slot = 0; ph ^= 1; }
            }
            TS(3);
        } else if (wid >= 1) {
            mbar_wait(sb + B_Q, 0);
            if (tid == 32) {
                l2_prefetch(reinterpret_cast<const uint8_t*>(p.wo) + cta * 2304, 2304);
                l2_prefetch(reinterpret_cast<const uint8_t*>(p.wkv) + cta * 4608, 4608);
            }
            {
                static_assert(X_END % (4 * NCTA) == 0, "");
                constexpr int ZN = X_END / 4 / NCTA;
                for (int i = tid - 32; i < ZN; i += 96) reinterpret_cast<uint4*>(g_x)[cta * ZN + i] = make_uint4(0, 0, 0, 0);
                if (tid - 32 < 48) g_act[(tag & 1) ^ 1][cta * 48 + tid - 32] = make_uint4(0, 0, 0, 0);
                __syncwarp();
                if (lane == 0) { fence_gpu(); mbar_arrive(sb + B_Z); }
            }
            const int hw = (cta - 32) * 3 + wid - 1;
            if (hw >= 0) wcomb(p, tag, hw, lane);
        }
        return;
    } else if (wid < 8) {
        float s[16], s2[16], slo[16], sl2[16];
        const uint32_t lq = dlB(sb + SM_Q);
        if (cta < NPRO) {
            if (cta >= 6) {
                const uint4* src = act + (cta < 12 ? 0 : 1536);
                fetch_img<12, 128>(sm + SM_Q, src, tid - 128);
            }
            bar_sync(1, 128);
            if (tid == 128) TS(14);
            mbar_wait(sb + B_FULL, 0); mbar_wait(sb + B_FULL + 8, 0);
            wg_fence();
            if (cta < 6) wgchain2<1, 1024, 24, 1, 2048, 0, 0, 0, 0>(s, s2, dlA(sb + SM_RING), lq);
            else wgchain2<0, 1024, 24, 4, 8192, 32, 0, 0, 0>(s, s2, dlA(sb + SM_RING), lq);
            wg_commit(); wg_wait0(); pin(s); pin(s2);
#pragma unroll
            for (int i = 0; i < 16; i++) s[i] += s2[i];
            if (lane < 2) { mbar_arrive(sb + B_EMPTY); mbar_arrive(sb + B_EMPTY + 8); }
            const float sc = cta < 12 ? 1.0f : 0.05103103630798288f * 1.4426950408889634f;
            uint32_t* dst = reinterpret_cast<uint32_t*>(const_cast<uint4*>(act)) + cta * 1024 + w * 256 + lane;
#pragma unroll
            for (int n = 0; n < 4; n++) {
                st_rlx(dst + 32 * n, ~movtrans(pack2(s[4 * n] * sc, s[4 * n + 1] * sc)));
                st_rlx(dst + 128 + 32 * n, ~movtrans(pack2(s[4 * n + 2] * sc, s[4 * n + 3] * sc)));
            }
            if (cta >= 12) { bar_sync(1, 128); if (tid == 128) st_rlx(&g_flagP[cta], tag); }
            if (tid == 128) TS(1);
        }
        if (w == 0) gate_img(12, 12, lane, flag0, tag);
        bar_sync(2, 384);
        fetch_img<8, 384>(sm + SM_Q, act + 2 * 1536, tid - 128);
        mbar_arrive(sb + B_Q);
        mbar_wait(sb + B_Q, 0);
        if (tid == 128) TS(2);
        float mth[8], lsum[8], pd[8], mlane = -INFINITY;
#pragma unroll
        for (int i = 0; i < 8; i++) { mth[i] = -INFINITY; lsum[i] = 0.f; pd[i] = 0.f; }
        float* wmax = reinterpret_cast<float*>(sm + SM_WMAX);
        float* alpha = reinterpret_cast<float*>(sm + SM_ALPHA);
        const int col = 8 * (lane >> 3) + 2 * t + (g & 1);
        for (int k = 0, go = 1; go; go = more_units(sb, k), k++) {
#pragma unroll
            for (int tb = 0; tb < 2; tb++) {
#pragma unroll
                for (int h = 0; h < 2; h++) {
                    const uint32_t ga = dlA(sb + SM_RING + slot * GB);
                    mbar_wait(sb + B_FULL + 8 * slot, ph);
                    if (++slot == NG) { slot = 0; ph ^= 1; }
                    wg_fence();
                    if (h == 0) wgchain2<0, 1024, 12, 4, 8192, 32, 0, 0, 0>(s, s2, ga, lq);
                    else wgchain2<0, 1024, 12, 4, 8192, 32, 0, 12288, 1>(s, s2, ga, lq);
                }
                if (tb == 0) {
                    const uint32_t gl = dlA(sb + SM_RING + slot * GB);
                    mbar_wait(sb + B_FULL + 8 * slot, ph);
                    if (++slot == NG) { slot = 0; ph ^= 1; }
                    wg_fence();
                    wgchain2<0, 512, 24, 4, 4096, 32, 0, GB, 0>(slo, sl2, gl, lq);
                }
                wg_commit(); wg_wait0(); pin(s); pin(s2);
                if (tb == 0) {
                    pin(slo); pin(sl2);
#pragma unroll
                    for (int i = 0; i < 16; i++) slo[i] += sl2[i];
                }
                float mx[8];
#pragma unroll
                for (int n = 0; n < 4; n++)
#pragma unroll
                    for (int i = 0; i < 2; i++) {
                        s[4 * n + i] += s2[4 * n + i] + slo[4 * n + i]; s[4 * n + 2 + i] += s2[4 * n + 2 + i] + slo[4 * n + i];
                        mx[2 * n + i] = fmaxf(s[4 * n + i], s[4 * n + 2 + i]);
                    }
                const bool b4 = lane & 16, b3 = lane & 8, b2 = lane & 4;
#pragma unroll
                for (int j = 0; j < 4; j++) mx[j] = fmaxf(b4 ? mx[4 + j] : mx[j], __shfl_xor_sync(~0u, b4 ? mx[j] : mx[4 + j], 16));
#pragma unroll
                for (int j = 0; j < 2; j++) mx[j] = fmaxf(b3 ? mx[2 + j] : mx[j], __shfl_xor_sync(~0u, b3 ? mx[j] : mx[2 + j], 8));
                const float cm = fmaxf(b2 ? mx[1] : mx[0], __shfl_xor_sync(~0u, b2 ? mx[0] : mx[1], 4));
                bar_sync(1, 128);
                wmax[w * 32 + col] = cm;
                bar_sync(1, 128);
                const float mnew = fmaxf(fmaxf(mlane, fmaxf(wmax[col], wmax[32 + col])), fmaxf(wmax[64 + col], wmax[96 + col]));
                mbar_wait(sb + B_PEMPTY + 8 * tb, (k & 1) ^ 1);
                if (w == 0) alpha[tb * 32 + col] = ex2(mlane - mnew);
                mlane = mnew;
                uint32_t pk[8];
#pragma unroll
                for (int n = 0; n < 4; n++) {
#pragma unroll
                    for (int i = 0; i < 2; i++) {
                        const int j = 2 * n + i;
                        const float mn = __shfl_sync(~0u, mnew, t + 4 * i + 8 * n);
                        const float a = ex2(mth[j] - mn);
                        mth[j] = mn;
                        const float p0 = ex2(s[4 * n + i] - mn), p1 = ex2(s[4 * n + 2 + i] - mn);
                        s[4 * n + i] = p0; s[4 * n + 2 + i] = p1;
                        lsum[j] = lsum[j] * a + (p0 + p1);
                        pd[j] = tb == 0 ? p0 + p1 : pd[j] * a + (p0 + p1);
                    }
                    pk[2 * n] = pack2(s[4 * n], s[4 * n + 1]); pk[2 * n + 1] = pack2(s[4 * n + 2], s[4 * n + 3]);
                }
                const uint32_t pa = sb + SM_P + tb * 4096 + (2 * w + ((lane >> 3) & 1)) * 512 + (8 * (lane >> 4) + (lane & 7)) * 16;
                stsm4t(pa, pk[0], pk[1], pk[2], pk[3]);
                stsm4t(pa + 256, pk[4], pk[5], pk[6], pk[7]);
                if (tb == 1) stsm4t(sb + SM_PD + w * 512 + lane * 16, pack2(pd[0], pd[1]), pack2(pd[2], pd[3]), pack2(pd[4], pd[5]), pack2(pd[6], pd[7]));
                fence_async_s();
                mbar_arrive(sb + B_PFULL + 8 * tb);
            }
        }
        {
            const bool b4 = lane & 16, b3 = lane & 8, b2 = lane & 4;
#pragma unroll
            for (int j = 0; j < 4; j++) lsum[j] = (b4 ? lsum[4 + j] : lsum[j]) + __shfl_xor_sync(~0u, b4 ? lsum[j] : lsum[4 + j], 16);
#pragma unroll
            for (int j = 0; j < 2; j++) lsum[j] = (b3 ? lsum[2 + j] : lsum[j]) + __shfl_xor_sync(~0u, b3 ? lsum[j] : lsum[2 + j], 8);
            const float cl = (b2 ? lsum[1] : lsum[0]) + __shfl_xor_sync(~0u, b2 ? lsum[0] : lsum[1], 4);
            bar_sync(1, 128);
            wmax[w * 32 + col] = cl;
            bar_sync(1, 128);
            float* ml = reinterpret_cast<float*>(sm + SM_Q);
            if (w == 0) { ml[col] = mlane; ml[32 + col] = (wmax[col] + wmax[32 + col]) + (wmax[64 + col] + wmax[96 + col]); }
            bar_sync(1, 128);
            const uint32_t par = tag & 1;
            const uint4 mv = reinterpret_cast<const uint4*>(ml)[(tid - 128) >> 4], lv = reinterpret_cast<const uint4*>(ml)[8 + ((tid - 128) >> 4)];
            uint4* o = &g_U[(cta * 128 + tid - 128) * 26 + 24];
            o[0] = make_uint4((mv.x & ~1u) | par, (mv.y & ~1u) | par, (mv.z & ~1u) | par, (mv.w & ~1u) | par);
            o[1] = make_uint4((lv.x & ~1u) | par, (lv.y & ~1u) | par, (lv.z & ~1u) | par, (lv.w & ~1u) | par);
            asm volatile("bar.arrive 3, 384;" ::: "memory");
        }
    } else {
        const int hf = (wid >> 2) - 2;
        bar_sync(2, 384);
        fetch_img<8, 384>(sm + SM_Q, act + 2 * 1536, tid - 128);
        mbar_arrive(sb + B_Q);
        float acc[6][16];
#pragma unroll
        for (int b = 0; b < 6; b++)
#pragma unroll
            for (int i = 0; i < 16; i++) acc[b][i] = 0.f;
        const float2* alpha = reinterpret_cast<const float2*>(sm + SM_ALPHA);
        const uint32_t lp = dlB(sb + SM_P);
        for (int k = 0, go = 1; go; go = more_units(sb, k), k++) {
            int sl = 0;
#pragma unroll
            for (int tb = 0; tb < 2; tb++) {
                const int s0 = slot; if (++slot == NG) { slot = 0; ph ^= 1; }
                const int s1 = slot; if (++slot == NG) { slot = 0; ph ^= 1; }
                if (tb == 0) { sl = slot; if (++slot == NG) { slot = 0; ph ^= 1; } }
                const uint32_t gh = dlA(sb + SM_RING + (hf ? s1 : s0) * GB), gl = dlA(sb + SM_RING + sl * GB + hf * 12288), lb = lp + tb * 256;
                mbar_wait(sb + B_PFULL + 8 * tb, k & 1);
#pragma unroll
                for (int n = 0; n < 4; n++) {
                    const float2 a = alpha[tb * 16 + 4 * n + t];
#pragma unroll
                    for (int b = 0; b < 6; b++) { acc[b][4 * n] *= a.x; acc[b][4 * n + 1] *= a.y; acc[b][4 * n + 2] *= a.x; acc[b][4 * n + 3] *= a.y; }
                }
                wg_fence();
                if (tb == 1) wgpv<2, 4096, 8192>(acc[3], acc[4], acc[5], gl, lp);
                wgpv<4, 8192, 0>(acc[0], acc[1], acc[2], gh, lb);
                wg_commit(); wg_wait0();
#pragma unroll
                for (int b = 0; b < 6; b++) pin(acc[b]);
                if (lane == 0) {
                    if (tb == 1) mbar_arrive(sb + B_EMPTY + 8 * sl);
                    mbar_arrive(sb + B_EMPTY + 8 * s0); mbar_arrive(sb + B_EMPTY + 8 * s1);
                    mbar_arrive(sb + B_PEMPTY + 8 * tb);
                }
            }
        }
        if (tid == 256) TS(4);
        uint2* ub = reinterpret_cast<uint2*>(g_U) + (size_t)cta * 128 * 52 + (t >> 1) * 16 * 52 + g * 2 + (t & 1);
        const uint32_t par = tag & 1;
#pragma unroll
        for (int b = 0; b < 6; b++) {
            const int si = 4 * ((b < 3 ? b : b + 3) + 3 * hf) + w, cs = si / 3, sub = si - 3 * cs;
#pragma unroll
            for (int n = 0; n < 4; n++) {
                const float x0 = __uint_as_float((__float_as_uint(acc[b][4 * n]) + 0x10000u) & 0xfffe0000u);
                ub[(2 * n * 16 + cs) * 52 + sub * 16] = make_uint2(pack2(x0, acc[b][4 * n + 1]) | par, pack2(acc[b][4 * n + 2], acc[b][4 * n + 3]));
            }
        }
        bar_sync(3, 384);
        if (tid == 256) { mbar_wait(sb + B_Z, 0); asm volatile("red.relaxed.gpu.global.add.u32 [%0], 1;" ::"l"(&g_gate) : "memory"); TS(5); }
    }
    tail(p, tag, sm, sb, slot, ph);
}

typedef CUresult (*EncFn)(CUtensorMap*, CUtensorMapDataType, cuuint32_t, void*, const cuuint64_t*, const cuuint64_t*, const cuuint32_t*,
                          const cuuint32_t*, CUtensorMapInterleave, CUtensorMapSwizzle, CUtensorMapL2promotion, CUtensorMapFloatOOBfill);
void enc(EncFn fn, CUtensorMap* m, const void* base, int rank, const cuuint64_t* dims, const cuuint64_t* str, const cuuint32_t* box,
         CUtensorMapSwizzle sw = CU_TENSOR_MAP_SWIZZLE_128B) {
    const cuuint32_t es[5] = {1, 1, 1, 1, 1};
    fn(m, CU_TENSOR_MAP_DATA_TYPE_BFLOAT16, rank, const_cast<void*>(base), dims, str, box, es, CU_TENSOR_MAP_INTERLEAVE_NONE,
       sw, CU_TENSOR_MAP_L2_PROMOTION_L2_256B, CU_TENSOR_MAP_FLOAT_OOB_FILL_NONE);
}
}

extern "C" void kernel_launch(void* const* d_in, const int* in_sizes, int n_in, void* d_out, int out_size) {
    static EncFn fn = nullptr;
    if (!fn) {
        cudaDriverEntryPointQueryResult qr;
        cudaGetDriverEntryPoint("cuTensorMapEncodeTiled", reinterpret_cast<void**>(&fn), cudaEnableDefault, &qr);
        cudaFuncSetAttribute(detr_kernel, cudaFuncAttributeMaxDynamicSharedMemorySize, SM_TOTAL);
    }
    Params p;
    p.q = (const bf16*)d_in[0]; p.fhi = (const bf16*)d_in[1]; p.flo = (const bf16*)d_in[2];
    p.lat_hi = (const bf16*)d_in[3]; p.lat_lo = (const bf16*)d_in[4];
    p.wkv = (const bf16*)d_in[6]; p.wo = (const bf16*)d_in[7]; p.w1 = (const bf16*)d_in[8]; p.w2 = (const bf16*)d_in[9];
    p.out = (bf16*)d_out;
    CUtensorMap mHi, mLo, mWq, mWk, mLh, mLl, mW1, mW2;
    { const cuuint64_t d[5] = {64, 8, 2, 9216, 6}, s[4] = {1536, 768, 12288, 128}; const cuuint32_t b[5] = {64, 8, 2, 4, 3}; enc(fn, &mHi, p.fhi, 5, d, s, b); }
    { const cuuint64_t d[3] = {64, 36864, 6}, s[2] = {768, 128}; const cuuint32_t b[3] = {64, 32, 6}; enc(fn, &mLo, p.flo, 3, d, s, b); }
    { const cuuint64_t d[2] = {384, 384}, s[1] = {768}; const cuuint32_t b[2] = {64, 192}; enc(fn, &mWq, d_in[5], 2, d, s, b); }
    { const cuuint64_t d[3] = {64, 384, 6}, s[2] = {1536, 128}; const cuuint32_t b[3] = {64, 64, 3}; enc(fn, &mWk, p.wkv, 3, d, s, b); }
    { const cuuint64_t d[3] = {64, 384, 6}, s[2] = {768, 128}; const cuuint32_t b[3] = {64, 64, 3};
      enc(fn, &mLh, p.lat_hi, 3, d, s, b); enc(fn, &mLl, p.lat_lo, 3, d, s, b); }
    { const cuuint64_t d[2] = {1536, 384}, s[1] = {3072}; const cuuint32_t b[2] = {64, 192}; enc(fn, &mW1, p.w1, 2, d, s, b); }
    { const cuuint64_t d[2] = {384, 1536}, s[1] = {768}; const cuuint32_t b[2] = {16, 256}; enc(fn, &mW2, p.w2, 2, d, s, b, CU_TENSOR_MAP_SWIZZLE_NONE); }
    detr_kernel<<<NCTA, 512, SM_TOTAL, cudaStreamPerThread>>>(mHi, mLo, mWq, mWk, mLh, mLl, mW1, mW2, p);
}
```

```cpp
#include <cuda_runtime.h>
#include <cuda_bf16.h>
#include <cuda.h>
#include <stdint.h>

namespace {
typedef __nv_bfloat16 bf16;
constexpr int C = 384, FF = 1536;
constexpr int NCTA = 128, NU = 1152;
constexpr int NG = 7, GB = 24576;
constexpr int NPRO = 24;
#define PACE 1
#define PFG 2
#define WCE 1
#define WCS 0
#define WCB 300
#define ACQF 0
#define PREP 1
#define FIX1 0
#define FIX2 0
#define WIN 3
#define WINK 7
#define WIN2 2
#define WINK2 7
#define NSTAT 4
#define CLAIM_J 3
#define STATIC 0
constexpr uint32_t SM_Q = 0, SM_RING = 49152, SM_P = SM_RING + NG * GB, SM_PD = SM_P + 8192,
                   SM_WMAX = SM_PD + 2048, SM_ALPHA = SM_WMAX + 512, SM_BAR = SM_ALPHA + 256,
                   SM_TOTAL = SM_BAR + 256;
static_assert(SM_TOTAL <= 232448, "smem");
constexpr uint32_t B_FULL = SM_BAR, B_EMPTY = B_FULL + 8 * NG, B_PFULL = B_EMPTY + 8 * NG,
                   B_PEMPTY = B_PFULL + 16, B_Q = B_PEMPTY + 16, B_Z = B_Q + 8, S_MORE = B_Z + 8, S_TAG = S_MORE + 16;
constexpr uint32_t SPIN_LIMIT = 1u << 22;

__device__ uint32_t g_epoch;
__device__ uint32_t g_cntW[2 * 32];
__device__ uint32_t g_next;
__device__ __align__(128) uint32_t g_flagP[32];
__device__ __align__(128) uint32_t g_done[NCTA];
__device__ uint4 g_act[2][4 * 1536];
__device__ __align__(16) uint32_t g_WvoT[C * C / 2];
__device__ uint4 g_WcF[16 * 72 * 32];
__device__ uint4 g_U[NCTA * 128 * 26];
constexpr int X_HP = 0, X_H = 16 * 32 * C, X_HN = X_H + 32 * C, X_A = X_HN + 32 * C / 2, X_END = X_A + 32 * FF / 2;
__device__ __align__(16) uint32_t g_x[X_END];
#define TS(i)

struct Params { const bf16 *q, *fhi, *flo, *lat_hi, *lat_lo, *wkv, *wo, *w1, *w2; bf16* out; };

__device__ __forceinline__ void mbar_init(uint32_t b, uint32_t n) { asm volatile("mbarrier.init.shared::cta.b64 [%0], %1;" ::"r"(b), "r"(n) : "memory"); }
__device__ __forceinline__ void mbar_arrive(uint32_t b) { asm volatile("mbarrier.arrive.shared::cta.b64 _, [%0];" ::"r"(b) : "memory"); }
__device__ __forceinline__ void mbar_expect(uint32_t b, uint32_t n) { asm volatile("mbarrier.arrive.expect_tx.shared::cta.b64 _, [%0], %1;" ::"r"(b), "r"(n) : "memory"); }
__device__ __forceinline__ void mbar_wait(uint32_t b, uint32_t par) {
    uint32_t ok, n = 0;
    do {
        asm volatile("{\n.reg .pred p;\nmbarrier.try_wait.parity.shared::cta.b64 p, [%1], %2;\nselp.u32 %0, 1, 0, p;\n}"
                     : "=r"(ok) : "r"(b), "r"(par) : "memory");
        if (++n > SPIN_LIMIT) __trap();
    } while (!ok);
}
__device__ __forceinline__ bool mbar_test(uint32_t b, uint32_t par) {
    uint32_t ok;
    asm volatile("{\n.reg .pred p;\nmbarrier.test_wait.parity.shared::cta.b64 p, [%1], %2;\nselp.u32 %0, 1, 0, p;\n}"
                 : "=r"(ok) : "r"(b), "r"(par) : "memory");
    return ok;
}
__device__ __forceinline__ void bar_sync(int id, int n) { asm volatile("bar.sync %0, %1;" ::"r"(id), "r"(n) : "memory"); }
__device__ __forceinline__ void fence_async() { asm volatile("fence.proxy.async;" ::: "memory"); }
__device__ __forceinline__ void fence_async_s() { asm volatile("fence.proxy.async.shared::cta;" ::: "memory"); }
__device__ __forceinline__ void fence_gpu() { asm volatile("fence.acq_rel.gpu;" ::: "memory"); }
__device__ __forceinline__ uint32_t ld_acq(const uint32_t* p) { uint32_t v; asm volatile("ld.acquire.gpu.global.u32 %0, [%1];" : "=r"(v) : "l"(p) : "memory"); return v; }
__device__ __forceinline__ uint32_t ld_rlx(const uint32_t* p) { uint32_t v; asm volatile("ld.relaxed.gpu.global.u32 %0, [%1];" : "=r"(v) : "l"(p) : "memory"); return v; }
__device__ __forceinline__ void st_rlx(uint32_t* p, uint32_t v) { asm volatile("st.relaxed.gpu.global.u32 [%0], %1;" ::"l"(p), "r"(v) : "memory"); }
__device__ __forceinline__ void poll_ge(const uint32_t* p, uint32_t tgt) {
    uint32_t n = 0;
    while ((int)(ld_acq(p) - tgt) < 0) { if (++n > SPIN_LIMIT) __trap(); }
}
__device__ __forceinline__ uint4 ld_rlx4(const void* p) {
    uint4 v; asm volatile("ld.relaxed.gpu.global.v4.u32 {%0, %1, %2, %3}, [%4];" : "=r"(v.x), "=r"(v.y), "=r"(v.z), "=r"(v.w) : "l"(p) : "memory");
    return v;
}
__device__ __forceinline__ bool nz4(const uint4& v) { return v.x && v.y && v.z && v.w; }
__device__ __forceinline__ uint4 poll4(const void* p) {
    uint4 v = ld_rlx4(p); uint32_t n = 0;
    while (!nz4(v)) { v = ld_rlx4(p); if (++n > SPIN_LIMIT) __trap(); }
    return v;
}
template <int N, int NT>
__device__ __forceinline__ void fetch_img(uint8_t* dst, const uint4* src, int i0) {
    uint4 v[N]; uint32_t n = 0; bool ok;
    if (FIX2) {
#pragma unroll
        for (int i = 0; i < N; i++) v[i] = make_uint4(0, 0, 0, 0);
    }
    do {
        ok = true;
#pragma unroll
        for (int i = 0; i < N; i++) if (!FIX2 || !nz4(v[i])) v[i] = ld_rlx4(src + i0 + i * NT);
#pragma unroll
        for (int i = 0; i < N; i++) ok = ok && nz4(v[i]);
        if (++n > SPIN_LIMIT) __trap();
    } while (!ok);
#pragma unroll
    for (int i = 0; i < N; i++) reinterpret_cast<uint4*>(dst)[i0 + i * NT] = make_uint4(~v[i].x, ~v[i].y, ~v[i].z, ~v[i].w);
    fence_async_s();
}
__device__ __forceinline__ void gate_img(int f0, int nblk, int lane, uint32_t first, uint32_t tag) {
    if (lane >= f0 && lane < f0 + nblk) { uint32_t n = 0; while (first != tag) { first = ld_rlx(&g_flagP[lane]); if (++n > SPIN_LIMIT) __trap(); } }
    __syncwarp();
}
__device__ __forceinline__ bool more_units(uint32_t sb, int k) {
    uint32_t v, n = 0;
    do {
        asm volatile("ld.volatile.shared.u32 %0, [%1];" : "=r"(v) : "r"(sb + S_MORE + 4 * (k & 3)) : "memory");
        if (++n > SPIN_LIMIT) __trap();
    } while ((int)(v >> 1) != k + 1);
    return v & 1;
}
__device__ __forceinline__ uint32_t pack2(float lo, float hi) { uint32_t r; asm("cvt.rn.bf16x2.f32 %0, %1, %2;" : "=r"(r) : "f"(hi), "f"(lo)); return r; }
__device__ __forceinline__ float bflo(uint32_t v) { return __uint_as_float(v << 16); }
__device__ __forceinline__ float bfhi(uint32_t v) { return __uint_as_float(v & 0xffff0000u); }
__device__ __forceinline__ float ex2(float x) { float r; asm("ex2.approx.ftz.f32 %0, %1;" : "=f"(r) : "f"(x)); return r; }
__device__ __forceinline__ uint32_t movtrans(uint32_t v) { uint32_t r; asm volatile("movmatrix.sync.aligned.m8n8.trans.b16 %0, %1;" : "=r"(r) : "r"(v)); return r; }
__device__ __forceinline__ void stsm4t(uint32_t a, uint32_t r0, uint32_t r1, uint32_t r2, uint32_t r3) {
    asm volatile("stmatrix.sync.aligned.m8n8.x4.trans.shared.b16 [%0], {%1, %2, %3, %4};" ::"r"(a), "r"(r0), "r"(r1), "r"(r2), "r"(r3) : "memory");
}
__device__ __forceinline__ uint4 ldsm4t(uint32_t a) {
    uint4 r; asm volatile("ldmatrix.sync.aligned.m8n8.x4.trans.shared.b16 {%0, %1, %2, %3}, [%4];" : "=r"(r.x), "=r"(r.y), "=r"(r.z), "=r"(r.w) : "r"(a) : "memory");
    return r;
}
__device__ __forceinline__ void mma16816(float (&d)[4], const uint32_t a0, const uint32_t a1, const uint32_t a2, const uint32_t a3, uint32_t b0, uint32_t b1) {
    asm volatile("mma.sync.aligned.m16n8k16.row.col.f32.bf16.bf16.f32 {%0,%1,%2,%3}, {%4,%5,%6,%7}, {%8,%9}, {%0,%1,%2,%3};"
                 : "+f"(d[0]), "+f"(d[1]), "+f"(d[2]), "+f"(d[3]) : "r"(a0), "r"(a1), "r"(a2), "r"(a3), "r"(b0), "r"(b1));
}
__device__ __forceinline__ uint32_t dlA(uint32_t a) { return (a >> 4) | (64u << 16); }
__device__ __forceinline__ uint32_t dlB(uint32_t a) { return (a >> 4) | (32u << 16); }
template <int TA, int SBO, int OA, int OB, int SC>
__device__ __forceinline__ void wgmma32(float (&d)[16], uint32_t la, uint32_t lb) {
    asm volatile("{\n.reg .pred p;\n.reg .b32 x, y;\n.reg .b64 da, db;\nsetp.ne.b32 p, %18, 0;\n"
                 "add.u32 x, %16, %20;\nadd.u32 y, %17, %21;\nmov.b64 da, {x, %22};\nmov.b64 db, {y, 8};\n"
                 "wgmma.mma_async.sync.aligned.m64n32k16.f32.bf16.bf16 "
                 "{%0,%1,%2,%3,%4,%5,%6,%7,%8,%9,%10,%11,%12,%13,%14,%15}, da, db, p, 1, 1, %19, 0;\n}"
                 : "+f"(d[0]), "+f"(d[1]), "+f"(d[2]), "+f"(d[3]), "+f"(d[4]), "+f"(d[5]), "+f"(d[6]), "+f"(d[7]),
                   "+f"(d[8]), "+f"(d[9]), "+f"(d[10]), "+f"(d[11]), "+f"(d[12]), "+f"(d[13]), "+f"(d[14]), "+f"(d[15])
                 : "r"(la), "r"(lb), "n"(SC), "n"(TA), "n"(OA >> 4), "n"(OB >> 4), "n"((SBO >> 4) | 0x40000000));
}
template <int TA, int SBO, int N, int PER, int CH, int ST, int OA, int OB, int SC0, int I = 0>
__device__ __forceinline__ void wgchain(float (&d)[16], uint32_t la, uint32_t lb) {
    if constexpr (I < N) {
        wgmma32<TA, SBO, OA + (I / PER) * CH + (I % PER) * ST, OB + I * 1024, (I == 0 ? SC0 : 1)>(d, la, lb);
        wgchain<TA, SBO, N, PER, CH, ST, OA, OB, SC0, I + 1>(d, la, lb);
    }
}
template <int TA, int SBO, int N, int PER, int CH, int ST, int OA, int OB, int SC0, int I = 0>
__device__ __forceinline__ void wgchain2(float (&d)[16], float (&e)[16], uint32_t la, uint32_t lb) {
    if constexpr (I < N) {
        wgmma32<TA, SBO, OA + (I / PER) * CH + (I % PER) * ST, OB + I * 1024, (I < 2 ? SC0 : 1)>(d, la, lb);
        wgchain2<TA, SBO, N, PER, CH, ST, OA, OB, SC0, I + 1>(e, d, la, lb);
    }
}
template <int N, int CH, int OB, int I = 0>
__device__ __forceinline__ void wgpv(float (&a)[16], float (&b)[16], float (&c)[16], uint32_t la, uint32_t lb) {
    if constexpr (I < N) {
        wgmma32<1, 1024, I * 2048, OB + I * 1024, 1>(a, la, lb);
        wgmma32<1, 1024, CH + I * 2048, OB + I * 1024, 1>(b, la, lb);
        wgmma32<1, 1024, 2 * CH + I * 2048, OB + I * 1024, 1>(c, la, lb);
        wgpv<N, CH, OB, I + 1>(a, b, c, la, lb);
    }
}
__device__ __forceinline__ void wg_fence() { asm volatile("wgmma.fence.sync.aligned;" ::: "memory"); }
__device__ __forceinline__ void wg_commit() { asm volatile("wgmma.commit_group.sync.aligned;" ::: "memory"); }
__device__ __forceinline__ void wg_wait0() { asm volatile("wgmma.wait_group.sync.aligned 0;" ::: "memory"); }
__device__ __forceinline__ void pin(float (&d)[16]) {
#pragma unroll
    for (int i = 0; i < 16; i++) asm volatile("" : "+f"(d[i])::"memory");
}
__device__ __forceinline__ void tma2(uint32_t dst, const CUtensorMap* m, int c0, int c1, uint32_t bar) {
    asm volatile("cp.async.bulk.tensor.2d.shared::cluster.global.mbarrier::complete_tx::bytes [%0], [%1, {%3, %4}], [%2];"
                 ::"r"(dst), "l"(m), "r"(bar), "r"(c0), "r"(c1) : "memory");
}
__device__ __forceinline__ void tma3(uint32_t dst, const CUtensorMap* m, int c1, int c2, uint32_t bar, uint64_t pol) {
    asm volatile("cp.async.bulk.tensor.3d.shared::cluster.global.mbarrier::complete_tx::bytes.L2::cache_hint [%0], [%1, {%3, %4, %5}], [%2], %6;"
                 ::"r"(dst), "l"(m), "r"(bar), "r"(0), "r"(c1), "r"(c2), "l"(pol) : "memory");
}
__device__ __forceinline__ void tma5(uint32_t dst, const CUtensorMap* m, int c3, int c4, uint32_t bar, uint64_t pol) {
    asm volatile("cp.async.bulk.tensor.5d.shared::cluster.global.mbarrier::complete_tx::bytes.L2::cache_hint [%0], [%1, {%3, %3, %3, %4, %5}], [%2], %6;"
                 ::"r"(dst), "l"(m), "r"(bar), "r"(0), "r"(c3), "r"(c4), "l"(pol) : "memory");
}
__device__ __forceinline__ void bulk_g2s(uint32_t dst, const void* src, uint32_t n, uint32_t bar) {
    asm volatile("cp.async.bulk.shared::cluster.global.mbarrier::complete_tx::bytes [%0], [%1], %2, [%3];" ::"r"(dst), "l"(src), "r"(n), "r"(bar) : "memory");
}
__device__ __forceinline__ void l2_prefetch(const void* src, uint32_t n) { asm volatile("cp.async.bulk.prefetch.L2.global [%0], %1;" ::"l"(src), "r"(n) : "memory"); }
__device__ __forceinline__ float wsum(float v) {
#pragma unroll
    for (int o = 16; o; o >>= 1) v += __shfl_xor_sync(~0u, v, o);
    return v;
}

__device__ __forceinline__ void tail(const Params& p, uint32_t tag, uint8_t* sm, uint32_t sb, int slot, int ph) {
    const int tid = threadIdx.x - 128, wid = tid >> 5, lane = tid & 31, g = lane >> 2, t = lane & 3, cta = blockIdx.x;
    const int rg = cta >> 4, cs = cta & 15;
    float* red = reinterpret_cast<float*>(sm + SM_RING + (slot ? slot - 1 : NG - 1) * GB);
    float4* redW = reinterpret_cast<float4*>(red + 3072);
    float4* redM = redW + 128;
    bf16* Us = reinterpret_cast<bf16*>(redM + 8);
    float* rs = reinterpret_cast<float*>(Us + 8 * 56);
    float* red2 = reinterpret_cast<float*>(sm + SM_Q + 1024);
    auto frag = [&](int gi) -> const uint4* {
        const int sl = slot + gi >= NG ? slot + gi - NG : slot + gi;
        mbar_wait(sb + B_FULL + 8 * sl, slot + gi >= NG ? ph ^ 1 : ph);
        return reinterpret_cast<const uint4*>(sm + SM_RING + sl * GB);
    };
    volatile uint32_t* msk = reinterpret_cast<volatile uint32_t*>(sm + SM_Q + 512);
    auto poll_done = [&]() -> bool {
        const uint4 f = ld_rlx4(&g_done[4 * lane]);
        const uint32_t b0 = __ballot_sync(~0u, f.x == tag), b1 = __ballot_sync(~0u, f.y == tag);
        const uint32_t b2 = __ballot_sync(~0u, f.z == tag), b3 = __ballot_sync(~0u, f.w == tag);
        if (lane < 4) msk[lane] = lane == 0 ? b0 : lane == 1 ? b1 : lane == 2 ? b2 : b3;
        __syncwarp();
        return (b0 & b1 & b2 & b3) != ~0u;
    };
    if (PREP) { if (wid == 0) poll_done(); } else if (tid < 4) msk[tid] = 0;
    bar_sync(2, 384);
    {
        const int pg = tid / 24, u = tid - pg * 24;
        const uint4* src = &g_U[(pg * 128 + cta) * 26] + u;
        const uint4* ml = &g_U[((tid & 127) * 128 + cta) * 26 + 24];
        const uint32_t par = tag & 1;
        uint4 v[8], m, l; uint32_t n = 0;
        {
            uint32_t todo = tid < 128 ? 0x11111113u : 0x11111111u;
            bool more = wid == 0;
            do {
                if (more && (!PREP || n)) more = poll_done();
                const uint32_t go = todo & (((msk[pg & 3] >> (pg >> 2)) & 0x11111111u) | (((msk[tid & 3] >> ((tid >> 2) & 31)) & 1) << 1));
#pragma unroll
                for (int i = 0; i < 8; i++) if (go >> (4 * i) & 1) v[i] = ld_rlx4(src + i * (16 * 128 * 26));
                if (go & 2) { m = ld_rlx4(ml); l = ld_rlx4(ml + 1); }
                todo &= ~go;
                if (++n > SPIN_LIMIT) __trap();
            } while (__any_sync(~0u, todo != 0) || more);
            if (ACQF && tid == 0) fence_gpu();
            if (tid == 0) TS(6);
        }
#define FM(x) __uint_as_float((x) & ~1u)
#define BAD4(v) ((((v).x ^ par) | ((v).y ^ par) | ((v).z ^ par) | ((v).w ^ par)) & 1)
        float4 mm, ll;
        if (tid < 128) {
            while (BAD4(m) | BAD4(l)) { m = ld_rlx4(ml); l = ld_rlx4(ml + 1); if (++n > SPIN_LIMIT) __trap(); }
            mm = make_float4(FM(m.x), FM(m.y), FM(m.z), FM(m.w)); ll = make_float4(FM(l.x), FM(l.y), FM(l.z), FM(l.w));
            float4 M = mm;
#pragma unroll
            for (int o = 16; o; o >>= 1) {
                M.x = fmaxf(M.x, __shfl_xor_sync(~0u, M.x, o)); M.y = fmaxf(M.y, __shfl_xor_sync(~0u, M.y, o));
                M.z = fmaxf(M.z, __shfl_xor_sync(~0u, M.z, o)); M.w = fmaxf(M.w, __shfl_xor_sync(~0u, M.w, o));
            }
            if (lane == 0) redM[wid] = M;
            bar_sync(1, 128);
            const float4 a = redM[0], b = redM[1], c = redM[2], d = redM[3];
            const float4 w4 = make_float4(ex2(mm.x - fmaxf(fmaxf(a.x, b.x), fmaxf(c.x, d.x))), ex2(mm.y - fmaxf(fmaxf(a.y, b.y), fmaxf(c.y, d.y))),
                                          ex2(mm.z - fmaxf(fmaxf(a.z, b.z), fmaxf(c.z, d.z))), ex2(mm.w - fmaxf(fmaxf(a.w, b.w), fmaxf(c.w, d.w))));
            redW[tid] = w4;
            const float4 L = make_float4(wsum(w4.x * ll.x), wsum(w4.y * ll.y), wsum(w4.z * ll.z), wsum(w4.w * ll.w));
            if (lane == 0) redM[4 + wid] = L;
        }
#pragma unroll
        for (int i = 0; i < 8; i++)
            while (((v[i].x ^ par) | (v[i].z ^ par)) & 1) { v[i] = ld_rlx4(src + i * (16 * 128 * 26)); if (++n > SPIN_LIMIT) __trap(); }
        bar_sync(2, 384);
        if (tid == 0) TS(12);
        float a[8] = {0, 0, 0, 0, 0, 0, 0, 0};
#pragma unroll
        for (int i = 0; i < 8; i++) {
            const float4 w = redW[pg + 16 * i];
            a[0] += w.x * bflo(v[i].x & ~1u); a[1] += w.y * bfhi(v[i].x); a[2] += w.x * bflo(v[i].y); a[3] += w.y * bfhi(v[i].y);
            a[4] += w.z * bflo(v[i].z & ~1u); a[5] += w.w * bfhi(v[i].z); a[6] += w.z * bflo(v[i].w); a[7] += w.w * bfhi(v[i].w);
        }
        float4* dst = reinterpret_cast<float4*>(red + pg * 192 + u * 8);
        dst[0] = make_float4(a[0], a[1], a[2], a[3]); dst[1] = make_float4(a[4], a[5], a[6], a[7]);
        if (tid < 112) reinterpret_cast<uint32_t*>(Us + 4 * 56)[tid] = 0;
        const uint4* wcp = frag(wid >= 8) + (wid & 7) * 192 + lane;
        uint4 wc[6];
#pragma unroll
        for (int i = 0; i < 6; i++) wc[i] = wcp[32 * i];
        bar_sync(2, 384);
        if (tid < 192) {
            const int j = tid & 7, uu = tid >> 3, ql = 2 * (j >> 2) + (j & 1), ch = 16 * (uu >> 3) + (uu & 7) + 8 * ((j >> 1) & 1);
            const float* pl = reinterpret_cast<const float*>(redM + 4) + ql;
            float num = 0;
#pragma unroll
            for (int i = 0; i < 16; i++) num += red[i * 192 + tid];
            Us[ql * 56 + ch] = __float2bfloat16(__fdividef(num, (pl[0] + pl[4]) + (pl[8] + pl[12])));
        }
        bar_sync(2, 384);
        const uint32_t* ub = reinterpret_cast<const uint32_t*>(Us + g * 56) + t;
#pragma unroll
        for (int j = 0; j < 2; j++) {
            float d[4] = {0, 0, 0, 0};
#pragma unroll
            for (int ks = 0; ks < 3; ks++) mma16816(d, wc[3 * j + ks].x, wc[3 * j + ks].y, wc[3 * j + ks].z, wc[3 * j + ks].w, ub[8 * ks], ub[8 * ks + 4]);
            if (t < 2) {
                uint32_t* o = &g_x[X_HP + (cs * 32 + 4 * rg + 2 * t) * C + 16 * (2 * wid + j) + g];
                st_rlx(o, ~__float_as_uint(d[0])); st_rlx(o + C, ~__float_as_uint(d[1]));
                st_rlx(o + 8, ~__float_as_uint(d[2])); st_rlx(o + C + 8, ~__float_as_uint(d[3]));
            }
        }
        if (tid == 0) TS(7);
    }
    if (cta >= 96) {
        const int q = cta - 96;
        const float qv = __bfloat162float(p.q[q * C + tid]);
        uint32_t v[16], n = 0; bool ok;
        do {
            ok = true;
#pragma unroll
            for (int i = 0; i < 16; i++) v[i] = ld_rlx(&g_x[X_HP + (i * 32 + q) * C + tid]);
#pragma unroll
            for (int i = 0; i < 16; i++) ok = ok && v[i];
            if (++n > SPIN_LIMIT) __trap();
        } while (!ok);
        float h = qv;
#pragma unroll
        for (int i = 0; i < 16; i++) h += __uint_as_float(~v[i]);
        st_rlx(&g_x[X_H + q * C + tid], ~__float_as_uint(h));
        const float mw = wsum(h) * (1.0f / 32), qw = wsum((h - mw) * (h - mw));
        if (lane == 0) { rs[wid] = mw; rs[16 + wid] = qw; }
        bar_sync(2, 384);
        float s = 0, s2 = 0;
#pragma unroll
        for (int i = 0; i < 12; i++) s += rs[i];
        s *= 1.0f / 12;
#pragma unroll
        for (int i = 0; i < 12; i++) s2 += rs[16 + i] + 32.0f * (rs[i] - s) * (rs[i] - s);
        const float dv = h - s;
        const float hn = dv * rsqrtf(s2 * (1.0f / C) + 1e-5f);
        const float hn1 = __shfl_down_sync(~0u, hn, 1);
        if (!(lane & 1)) st_rlx(&g_x[X_HN + q * (C / 2) + (tid >> 1)], ~pack2(hn, hn1));
        if (tid == 0) TS(8);
        return;
    }
    const int r4 = cta / 24, c24 = cta - r4 * 24;
    uint4 A1[8], A2[8];
    {
        const int kr = 8 * ((lane & 7) >> 1) + (lane & 1) + 2 * (lane >> 4), hi = (lane >> 3) & 1;
        const uint32_t f1 = (uint32_t)__cvta_generic_to_shared(frag(2 + (wid >= 6))) + (32 * (wid % 6) + kr) * 128;
        const uint32_t f2 = (uint32_t)__cvta_generic_to_shared(frag(4 + (wid >= 6))) + (128 * (wid % 6) + kr) * 32 + hi * 16;
#pragma unroll
        for (int s = 0; s < 8; s++) {
            A1[s] = ldsm4t(f1 + (s & 1) * 512 + (((2 * (s >> 1) + hi) ^ ((kr + 4 * (s & 1)) & 7)) << 4));
            A2[s] = ldsm4t(f2 + (32 * (s >> 1) + 4 * (s & 1)) * 32);
        }
    }
    {
        const uint4 b = poll4(&g_x[X_HN + (8 * r4 + g) * (C / 2) + 16 * wid + 4 * t]);
        __syncwarp();
        if (tid == 0) TS(8);
#pragma unroll
        for (int mt = 0; mt < 4; mt++) {
            float d[4] = {0, 0, 0, 0};
            mma16816(d, A1[2 * mt].x, A1[2 * mt].y, A1[2 * mt].z, A1[2 * mt].w, ~b.x, ~b.y);
            mma16816(d, A1[2 * mt + 1].x, A1[2 * mt + 1].y, A1[2 * mt + 1].z, A1[2 * mt + 1].w, ~b.z, ~b.w);
            float* o = red2 + (wid * 8 + 2 * t) * 68 + 16 * mt + g;
            o[0] = d[0]; o[68] = d[1]; o[8] = d[2]; o[76] = d[3];
        }
        bar_sync(2, 384);
        if (tid < 256) {
            const float2* r2 = reinterpret_cast<const float2*>(red2 + wid * 68) + lane;
            float x = 0, y = 0;
#pragma unroll
            for (int i = 0; i < 12; i++) { const float2 z = r2[i * 272]; x += z.x; y += z.y; }
            const float ex = __expf(-1.5957691216057308f * (x + 0.044715f * x * x * x)), ey = __expf(-1.5957691216057308f * (y + 0.044715f * y * y * y));
            st_rlx(&g_x[X_A + (8 * r4 + wid) * (FF / 2) + 32 * c24 + lane], ~pack2(x / (1.0f + ex), y / (1.0f + ey)));
        }
        if (tid == 0) TS(9);
    }
    {
        const int oq = 8 * r4 + (tid >> 3), oc = 16 * c24 + 2 * (tid & 7);
        const uint32_t* src = &g_x[X_A + (8 * r4 + g) * (FF / 2) + 64 * wid + 4 * t];
        uint4 b[4];
        b[0] = poll4(src);
#pragma unroll
        for (int j = 1; j < 4; j++) b[j] = ld_rlx4(src + 16 * j);
        uint32_t h0 = 1, h1 = 1;
        if (tid < 64) { h0 = ld_rlx(&g_x[X_H + oq * C + oc]); h1 = ld_rlx(&g_x[X_H + oq * C + oc + 1]); }
#pragma unroll
        for (int j = 1; j < 4; j++) if (!nz4(b[j])) b[j] = poll4(src + 16 * j);
        __syncwarp();
        if (tid == 0) TS(10);
        float d[4] = {0, 0, 0, 0}, e[4] = {0, 0, 0, 0};
#pragma unroll
        for (int j = 0; j < 4; j++) {
            mma16816(d, A2[2 * j].x, A2[2 * j].y, A2[2 * j].z, A2[2 * j].w, ~b[j].x, ~b[j].y);
            mma16816(e, A2[2 * j + 1].x, A2[2 * j + 1].y, A2[2 * j + 1].z, A2[2 * j + 1].w, ~b[j].z, ~b[j].w);
        }
        float* o = red + (wid * 8 + 2 * t) * 20 + g;
        o[0] = d[0] + e[0]; o[20] = d[1] + e[1]; o[8] = d[2] + e[2]; o[28] = d[3] + e[3];
        bar_sync(2, 384);
        if (tid < 64) {
            uint32_t n = 0;
            while (!h0 || !h1) { h0 = ld_rlx(&g_x[X_H + oq * C + oc]); h1 = ld_rlx(&g_x[X_H + oq * C + oc + 1]); if (++n > SPIN_LIMIT) __trap(); }
            float x = __uint_as_float(~h0), y = __uint_as_float(~h1);
            const float2* r = reinterpret_cast<const float2*>(red + (tid >> 3) * 20) + (tid & 7);
#pragma unroll
            for (int i = 0; i < 12; i++) { const float2 z = r[80 * i]; x += z.x; y += z.y; }
            *reinterpret_cast<uint32_t*>(p.out + oq * C + oc) = pack2(x, y);
        }
        if (tid == 0) { if (cta == 0) { st_rlx(&g_next, 0); st_rlx(&g_epoch, tag); } TS(11); }
    }
}

__device__ __forceinline__ void wcomb(const Params& p, volatile uint32_t* stag, int hw, int lane, uint32_t sbq) {
    const int g = lane >> 2, t = lane & 3, mt = hw % 24, grp = hw / 24;
    {
        float d[4][4] = {};
        const bf16* wv = p.wkv + (size_t)(32 * grp + g) * (2 * C) + C + 8 * t;
        const uint32_t* wo = reinterpret_cast<const uint32_t*>(p.wo + (8 * (g >> 1) + (g & 1)) * C + 16 * mt) + t;
#pragma unroll 1
        for (int k3 = 0; k3 < 12; k3 += 3) {
            uint32_t a[3][8]; uint4 b[3][4];
#pragma unroll
            for (int kk = 0; kk < 3; kk++) {
#pragma unroll
                for (int i = 0; i < 8; i++) a[kk][i] = __ldg(wo + (32 * (k3 + kk) + 2 * (i >> 1)) * (C / 2) + 4 * (i & 1));
#pragma unroll
                for (int j = 0; j < 4; j++) b[kk][j] = __ldg(reinterpret_cast<const uint4*>(wv + (size_t)j * 8 * 2 * C + 32 * (k3 + kk)));
            }
#pragma unroll
            for (int kk = 0; kk < 3; kk++) {
#pragma unroll
                for (int i = 0; i < 8; i++) a[kk][i] = movtrans(a[kk][i]);
#pragma unroll
                for (int j = 0; j < 4; j++) {
                    mma16816(d[j], a[kk][0], a[kk][1], a[kk][2], a[kk][3], b[kk][j].x, b[kk][j].y);
                    mma16816(d[j], a[kk][4], a[kk][5], a[kk][6], a[kk][7], b[kk][j].z, b[kk][j].w);
                }
            }
        }
#pragma unroll
        for (int j = 0; j < 4; j++) {
            uint32_t* o = &g_WvoT[(16 * mt + g) * (C / 2) + 16 * grp + 4 * j + t];
            o[0] = pack2(d[j][0], d[j][1]); o[8 * (C / 2)] = pack2(d[j][2], d[j][3]);
        }
        __syncwarp();
        if (lane == 0) { fence_gpu(); atomicAdd(&g_cntW[0], 1u);
            if (WCS) mbar_wait(sbq, 0);
            uint32_t n = 0;
            while ((int)(ld_acq(&g_cntW[0]) - *stag * 288u) < 0) { if (WCB) __nanosleep(WCB); if (++n > SPIN_LIMIT) __trap(); }
            TS(15);
        }
        __syncwarp();
    }
    {
        float d[8][4] = {};
        const bf16* lat = (grp < 6 ? p.lat_hi + (size_t)(64 * grp) * C : p.lat_lo + (size_t)(64 * (grp - 6)) * C) + g * C + 8 * t;
        const uint4* wa = reinterpret_cast<const uint4*>(g_WvoT) + (16 * mt + g) * 48 + t;
#pragma unroll 1
        for (int k2 = 0; k2 < 12; k2 += 2) {
            uint4 a[2][2], b[2][8];
#pragma unroll
            for (int kk = 0; kk < 2; kk++) {
                a[kk][0] = __ldcg(wa + 4 * (k2 + kk)); a[kk][1] = __ldcg(wa + 8 * 48 + 4 * (k2 + kk));
#pragma unroll
                for (int j = 0; j < 8; j++) b[kk][j] = __ldg(reinterpret_cast<const uint4*>(lat + j * 8 * C + 32 * (k2 + kk)));
            }
#pragma unroll
            for (int kk = 0; kk < 2; kk++)
#pragma unroll
                for (int j = 0; j < 8; j++) {
                    mma16816(d[j], a[kk][0].x, a[kk][1].x, a[kk][0].y, a[kk][1].y, b[kk][j].x, b[kk][j].y);
                    mma16816(d[j], a[kk][0].z, a[kk][1].z, a[kk][0].w, a[kk][1].w, b[kk][j].z, b[kk][j].w);
                }
        }
#pragma unroll
        for (int j = 0; j < 4; j++)
            g_WcF[(((4 * grp + j) / 3) * 72 + mt * 3 + (4 * grp + j) % 3) * 32 + lane] = make_uint4(pack2(d[2 * j][0], d[2 * j][1]), pack2(d[2 * j][2], d[2 * j][3]),
                                                                   pack2(d[2 * j + 1][0], d[2 * j + 1][1]), pack2(d[2 * j + 1][2], d[2 * j + 1][3]));
        __syncwarp();
        fence_async();
        __syncwarp();
        if (lane == 0) { fence_gpu(); atomicAdd(&g_cntW[32], 1u); TS(13); }
    }
}

__global__ void __launch_bounds__(512, 1)
detr_kernel(const __grid_constant__ CUtensorMap tmHi, const __grid_constant__ CUtensorMap tmLo,
            const __grid_constant__ CUtensorMap tmWq, const __grid_constant__ CUtensorMap tmWk,
            const __grid_constant__ CUtensorMap tmLh, const __grid_constant__ CUtensorMap tmLl,
            const __grid_constant__ CUtensorMap tmW1, const __grid_constant__ CUtensorMap tmW2, const Params p) {
    extern __shared__ __align__(1024) uint8_t sm[];
    const uint32_t sb = (uint32_t)__cvta_generic_to_shared(sm);
    const int tid = threadIdx.x, wid = tid >> 5, lane = tid & 31, cta = blockIdx.x;
    const int g = lane >> 2, t = lane & 3, w = wid & 3;
    const int pos0 = cta < NPRO ? 2 : 0;
    const uint32_t epoch = ld_rlx(&g_epoch);
    int slot = pos0, ph = 0;
    if (tid == 0) {
        TS(0);
        if (sb & 1023) __trap();
        for (int i = 0; i < NG; i++) { mbar_init(sb + B_FULL + 8 * i, 1); mbar_init(sb + B_EMPTY + 8 * i, 8); }
        for (int i = 0; i < 2; i++) { mbar_init(sb + B_PFULL + 8 * i, 128); mbar_init(sb + B_PEMPTY + 8 * i, 8); }
        mbar_init(sb + B_Q, 384); mbar_init(sb + B_Z, 3);
        *reinterpret_cast<uint4*>(sm + S_MORE) = make_uint4(0, 0, 0, 0);
        asm volatile("fence.mbarrier_init.release.cluster;" ::: "memory");
        if (FIX1) fence_async_s(); else fence_async();
            if (cta < NPRO) {
                uint64_t poln; asm volatile("createpolicy.fractional.L2::evict_normal.b64 %0, 1.0;" : "=l"(poln));
                for (int h = 0; h < 2; h++) {
                    const uint32_t dst = sb + SM_RING + h * GB, bar = sb + B_FULL + 8 * h;
                    mbar_expect(bar, GB);
                    if (cta < 6) tma2(dst, &tmWq, 64 * cta, 192 * h, bar);
                    else if (cta < 12) tma3(dst, &tmWk, 64 * (cta - 6), 3 * h, bar, poln);
                    else if (cta < 18) tma3(dst, &tmLh, 64 * (cta - 12), 3 * h, bar, poln);
                    else tma3(dst, &tmLl, 64 * (cta - 18), 3 * h, bar, poln);
                }
            }
    }
    if (cta < 6 && (wid >> 2) == 1) {
        const int row = (tid & 127) >> 2;
        uint4 x[12];
#pragma unroll
        for (int j = 0; j < 12; j++) x[j] = __ldg(reinterpret_cast<const uint4*>(p.q + row * C) + 4 * j + t);
                float sum = 0;
#pragma unroll
                for (int j = 0; j < 12; j++) sum += ((bflo(x[j].x) + bfhi(x[j].x)) + (bflo(x[j].y) + bfhi(x[j].y))) + ((bflo(x[j].z) + bfhi(x[j].z)) + (bflo(x[j].w) + bfhi(x[j].w)));
                sum += __shfl_xor_sync(~0u, sum, 1); sum += __shfl_xor_sync(~0u, sum, 2);
                const float mean = sum * (1.0f / C);
                float var = 0;
#define SQ2(v) ((bflo(v) - mean) * (bflo(v) - mean) + (bfhi(v) - mean) * (bfhi(v) - mean))
#pragma unroll
                for (int j = 0; j < 12; j++) var += (SQ2(x[j].x) + SQ2(x[j].y)) + (SQ2(x[j].z) + SQ2(x[j].w));
                var += __shfl_xor_sync(~0u, var, 1); var += __shfl_xor_sync(~0u, var, 2);
                const float rstd = rsqrtf(var * (1.0f / C) + 1e-5f);
#define NRM(v) pack2((bflo(v) - mean) * rstd, (bfhi(v) - mean) * rstd)
#pragma unroll
                for (int j = 0; j < 12; j++)
                    *reinterpret_cast<uint4*>(sm + SM_Q + (4 * j + t) * 512 + row * 16) = make_uint4(NRM(x[j].x), NRM(x[j].y), NRM(x[j].z), NRM(x[j].w));
                fence_async_s();
    }
    __syncthreads();
    volatile uint32_t* stag = reinterpret_cast<volatile uint32_t*>(sm + S_TAG);
    if (wid) *stag = epoch + 1;

    if (wid < 4) {
        if (tid == 0) {
            uint64_t pol; asm volatile("createpolicy.fractional.L2::evict_first.b64 %0, 1.0;" : "=l"(pol));
            int cnt = pos0, U = cta, Un = NCTA + cta;
            ph = 1;
            for (int k = 0; U < NU; k++) {
                const int b0 = (U / 6) * 48 + 4 * (U % 6);
#pragma unroll 1
                for (int j = 0; j < 5; j++) {
                    if (cnt >= PACE && cnt < NG) mbar_wait(sb + B_FULL + 8 * (cnt - PACE), 0);
                    if (PFG && cnt == NG) {
                        const uint8_t* prev = nullptr;
                        for (int n = NG - pos0; n < NG - pos0 + PFG && n < 5 * NSTAT; n++) {
                            const int UU = (n / 5) * NCTA + cta, jj = n % 5, bb = (UU / 6) * 48 + 4 * (UU % 6);
                            const uint8_t* src = jj == 2 ? reinterpret_cast<const uint8_t*>(p.flo + (size_t)UU * 32 * C)
                                : reinterpret_cast<const uint8_t*>(p.fhi + (size_t)(bb + (jj > 2 ? 24 : 0)) * 16 * C) + ((jj == 1 || jj == 4) ? GB : 0);
                            if (!prev) mbar_wait(sb + B_FULL + 8 * (NG - PACE), 0);
                            if (mbar_test(sb + B_Q, 0)) break;
                            l2_prefetch(src, GB);
                            if (prev) { if (ld_rlx(reinterpret_cast<const uint32_t*>(prev + GB - 4)) == 0x9e3779b9u) __nanosleep(1); }
                            else mbar_wait(sb + B_FULL + 8 * (NG - 1), 0);
                            prev = src;
                        }
                    }
                    const uint32_t dst = sb + SM_RING + slot * GB, bar = sb + B_FULL + 8 * slot;
                    mbar_wait(sb + B_EMPTY + 8 * slot, ph);
                    if (cnt >= NG && k >= WINK) {
                        const int c = cnt - (k >= WINK2 ? WIN2 : WIN);
                        mbar_wait(sb + B_FULL + 8 * (c % NG), (c / NG) & 1);
                    }
                    cnt++;
                    if (j == CLAIM_J) Un = (STATIC || k < NSTAT - 1) ? U + NCTA : NSTAT * NCTA + (int)atomicAdd(&g_next, 1u);
                    mbar_expect(bar, GB);
                    if (j == 2) tma3(dst, &tmLo, 32 * U, 0, bar, pol);
                    else tma5(dst, &tmHi, b0 + (j > 2 ? 24 : 0), (j == 1 || j == 4) ? 3 : 0, bar, pol);
                    if (++slot == NG) { slot = 0; ph ^= 1; }
                }
                if (k == 5) {
                    l2_prefetch(reinterpret_cast<const uint8_t*>(p.w1) + cta * 9216, 9216);
                    l2_prefetch(reinterpret_cast<const uint8_t*>(p.w2) + cta * 9216, 9216);
                }
                U = Un;
                asm volatile("st.volatile.shared.u32 [%0], %1;" ::"r"(sb + S_MORE + 4 * (k & 3)), "r"(2 * (k + 1) + (U < NU)) : "memory");
            }
            poll_ge(&g_cntW[32], *stag * 288u);
            fence_async();
            for (int j = 0; j < (cta < 96 ? 6 : 2); j++) {
                const uint32_t bytes = j == 1 ? GB / 2 : GB, bar = sb + B_FULL + 8 * slot;
                const uint32_t dst = sb + SM_RING + slot * GB;
                mbar_wait(sb + B_EMPTY + 8 * slot, ph);
                mbar_expect(bar, bytes);
                if (j < 2) bulk_g2s(dst, &g_WcF[(cta & 15) * 2304 + j * 1536], bytes, bar);
                else if (j < 4) tma2(dst, &tmW1, 64 * (cta % 24), 192 * (j - 2), bar);
                else for (int i = 0; i < 3; i++) tma2(dst + i * 8192, &tmW2, 16 * (cta % 24), 768 * (j - 4) + 256 * i, bar);
                if (++slot == NG) { slot = 0; ph ^= 1; }
            }
            TS(3);
        } else if (wid >= 1) {
            const int hw = (cta - 32) * 3 + wid - 1;
            if (WCE && hw >= 0) { if (WCE > 1) __nanosleep(WCE); wcomb(p, stag, hw, lane, sb + B_Q); }
            mbar_wait(sb + B_Q, 0);
            if (!WCE && tid == 32) {
                l2_prefetch(reinterpret_cast<const uint8_t*>(p.wo) + cta * 2304, 2304);
                l2_prefetch(reinterpret_cast<const uint8_t*>(p.wkv) + cta * 4608, 4608);
            }
            {
                static_assert(X_END % (4 * NCTA) == 0, "");
                constexpr int ZN = X_END / 4 / NCTA;
                for (int i = tid - 32; i < ZN; i += 96) reinterpret_cast<uint4*>(g_x)[cta * ZN + i] = make_uint4(0, 0, 0, 0);
                if (tid - 32 < 48) g_act[(*stag & 1) ^ 1][cta * 48 + tid - 32] = make_uint4(0, 0, 0, 0);
                __syncwarp();
                if (lane == 0) { fence_gpu(); mbar_arrive(sb + B_Z); }
            }
            if (!WCE && hw >= 0) wcomb(p, stag, hw, lane, sb + B_Q);
        }
        return;
    } else if (wid < 8) {
        float s[16], s2[16], slo[16], sl2[16];
        const uint32_t lq = dlB(sb + SM_Q);
        if (cta < NPRO) {
            if (cta >= 6) {
                const uint4* src = g_act[*stag & 1] + (cta < 12 ? 0 : 1536);
                fetch_img<12, 128>(sm + SM_Q, src, tid - 128);
            }
            bar_sync(1, 128);
            if (tid == 128) TS(14);
            mbar_wait(sb + B_FULL, 0); mbar_wait(sb + B_FULL + 8, 0);
            wg_fence();
            if (cta < 6) wgchain2<1, 1024, 24, 1, 2048, 0, 0, 0, 0>(s, s2, dlA(sb + SM_RING), lq);
            else wgchain2<0, 1024, 24, 4, 8192, 32, 0, 0, 0>(s, s2, dlA(sb + SM_RING), lq);
            wg_commit(); wg_wait0(); pin(s); pin(s2);
#pragma unroll
            for (int i = 0; i < 16; i++) s[i] += s2[i];
            if (lane < 2) { mbar_arrive(sb + B_EMPTY); mbar_arrive(sb + B_EMPTY + 8); }
            const float sc = cta < 12 ? 1.0f : 0.05103103630798288f * 1.4426950408889634f;
            uint32_t* dst = reinterpret_cast<uint32_t*>(const_cast<uint4*>(g_act[*stag & 1])) + cta * 1024 + w * 256 + lane;
#pragma unroll
            for (int n = 0; n < 4; n++) {
                st_rlx(dst + 32 * n, ~movtrans(pack2(s[4 * n] * sc, s[4 * n + 1] * sc)));
                st_rlx(dst + 128 + 32 * n, ~movtrans(pack2(s[4 * n + 2] * sc, s[4 * n + 3] * sc)));
            }
            if (cta >= 12) { bar_sync(1, 128); if (tid == 128) st_rlx(&g_flagP[cta], *stag); }
            if (tid == 128) TS(1);
        }
        if (w == 0) gate_img(12, 12, lane, ld_rlx(&g_flagP[lane]), *stag);
        bar_sync(2, 384);
        fetch_img<8, 384>(sm + SM_Q, g_act[*stag & 1] + 2 * 1536, tid - 128);
        mbar_arrive(sb + B_Q);
        mbar_wait(sb + B_Q, 0);
        if (tid == 128) TS(2);
        float mth[8], lsum[8], pd[8], mlane = -INFINITY;
#pragma unroll
        for (int i = 0; i < 8; i++) { mth[i] = -INFINITY; lsum[i] = 0.f; pd[i] = 0.f; }
        float* wmax = reinterpret_cast<float*>(sm + SM_WMAX);
        float* alpha = reinterpret_cast<float*>(sm + SM_ALPHA);
        const int col = 8 * (lane >> 3) + 2 * t + (g & 1);
        for (int k = 0, go = 1; go; go = more_units(sb, k), k++) {
#pragma unroll
            for (int tb = 0; tb < 2; tb++) {
#pragma unroll
                for (int h = 0; h < 2; h++) {
                    const uint32_t ga = dlA(sb + SM_RING + slot * GB);
                    mbar_wait(sb + B_FULL + 8 * slot, ph);
                    if (++slot == NG) { slot = 0; ph ^= 1; }
                    wg_fence();
                    if (h == 0) wgchain2<0, 1024, 12, 4, 8192, 32, 0, 0, 0>(s, s2, ga, lq);
                    else wgchain2<0, 1024, 12, 4, 8192, 32, 0, 12288, 1>(s, s2, ga, lq);
                }
                if (tb == 0) {
                    const uint32_t gl = dlA(sb + SM_RING + slot * GB);
                    mbar_wait(sb + B_FULL + 8 * slot, ph);
                    if (++slot == NG) { slot = 0; ph ^= 1; }
                    wg_fence();
                    wgchain2<0, 512, 24, 4, 4096, 32, 0, GB, 0>(slo, sl2, gl, lq);
                }
                wg_commit(); wg_wait0(); pin(s); pin(s2);
                if (tb == 0) {
                    pin(slo); pin(sl2);
#pragma unroll
                    for (int i = 0; i < 16; i++) slo[i] += sl2[i];
                }
                float mx[8];
#pragma unroll
                for (int n = 0; n < 4; n++)
#pragma unroll
                    for (int i = 0; i < 2; i++) {
                        s[4 * n + i] += s2[4 * n + i] + slo[4 * n + i]; s[4 * n + 2 + i] += s2[4 * n + 2 + i] + slo[4 * n + i];
                        mx[2 * n + i] = fmaxf(s[4 * n + i], s[4 * n + 2 + i]);
                    }
                const bool b4 = lane & 16, b3 = lane & 8, b2 = lane & 4;
#pragma unroll
                for (int j = 0; j < 4; j++) mx[j] = fmaxf(b4 ? mx[4 + j] : mx[j], __shfl_xor_sync(~0u, b4 ? mx[j] : mx[4 + j], 16));
#pragma unroll
                for (int j = 0; j < 2; j++) mx[j] = fmaxf(b3 ? mx[2 + j] : mx[j], __shfl_xor_sync(~0u, b3 ? mx[j] : mx[2 + j], 8));
                const float cm = fmaxf(b2 ? mx[1] : mx[0], __shfl_xor_sync(~0u, b2 ? mx[0] : mx[1], 4));
                bar_sync(1, 128);
                wmax[w * 32 + col] = cm;
                bar_sync(1, 128);
                const float mnew = fmaxf(fmaxf(mlane, fmaxf(wmax[col], wmax[32 + col])), fmaxf(wmax[64 + col], wmax[96 + col]));
                mbar_wait(sb + B_PEMPTY + 8 * tb, (k & 1) ^ 1);
                if (w == 0) alpha[tb * 32 + col] = ex2(mlane - mnew);
                mlane = mnew;
                uint32_t pk[8];
#pragma unroll
                for (int n = 0; n < 4; n++) {
#pragma unroll
                    for (int i = 0; i < 2; i++) {
                        const int j = 2 * n + i;
                        const float mn = __shfl_sync(~0u, mnew, t + 4 * i + 8 * n);
                        const float a = ex2(mth[j] - mn);
                        mth[j] = mn;
                        const float p0 = ex2(s[4 * n + i] - mn), p1 = ex2(s[4 * n + 2 + i] - mn);
                        s[4 * n + i] = p0; s[4 * n + 2 + i] = p1;
                        lsum[j] = lsum[j] * a + (p0 + p1);
                        pd[j] = tb == 0 ? p0 + p1 : pd[j] * a + (p0 + p1);
                    }
                    pk[2 * n] = pack2(s[4 * n], s[4 * n + 1]); pk[2 * n + 1] = pack2(s[4 * n + 2], s[4 * n + 3]);
                }
                const uint32_t pa = sb + SM_P + tb * 4096 + (2 * w + ((lane >> 3) & 1)) * 512 + (8 * (lane >> 4) + (lane & 7)) * 16;
                stsm4t(pa, pk[0], pk[1], pk[2], pk[3]);
                stsm4t(pa + 256, pk[4], pk[5], pk[6], pk[7]);
                if (tb == 1) stsm4t(sb + SM_PD + w * 512 + lane * 16, pack2(pd[0], pd[1]), pack2(pd[2], pd[3]), pack2(pd[4], pd[5]), pack2(pd[6], pd[7]));
                fence_async_s();
                mbar_arrive(sb + B_PFULL + 8 * tb);
            }
        }
        {
            const bool b4 = lane & 16, b3 = lane & 8, b2 = lane & 4;
#pragma unroll
            for (int j = 0; j < 4; j++) lsum[j] = (b4 ? lsum[4 + j] : lsum[j]) + __shfl_xor_sync(~0u, b4 ? lsum[j] : lsum[4 + j], 16);
#pragma unroll
            for (int j = 0; j < 2; j++) lsum[j] = (b3 ? lsum[2 + j] : lsum[j]) + __shfl_xor_sync(~0u, b3 ? lsum[j] : lsum[2 + j], 8);
            const float cl = (b2 ? lsum[1] : lsum[0]) + __shfl_xor_sync(~0u, b2 ? lsum[0] : lsum[1], 4);
            bar_sync(1, 128);
            wmax[w * 32 + col] = cl;
            bar_sync(1, 128);
            float* ml = reinterpret_cast<float*>(sm + SM_Q);
            if (w == 0) { ml[col] = mlane; ml[32 + col] = (wmax[col] + wmax[32 + col]) + (wmax[64 + col] + wmax[96 + col]); }
            bar_sync(1, 128);
            const uint32_t par = *stag & 1;
            const uint4 mv = reinterpret_cast<const uint4*>(ml)[(tid - 128) >> 4], lv = reinterpret_cast<const uint4*>(ml)[8 + ((tid - 128) >> 4)];
            uint4* o = &g_U[(cta * 128 + tid - 128) * 26 + 24];
            o[0] = make_uint4((mv.x & ~1u) | par, (mv.y & ~1u) | par, (mv.z & ~1u) | par, (mv.w & ~1u) | par);
            o[1] = make_uint4((lv.x & ~1u) | par, (lv.y & ~1u) | par, (lv.z & ~1u) | par, (lv.w & ~1u) | par);
            asm volatile("bar.arrive 3, 384;" ::: "memory");
        }
    } else {
        const int hf = (wid >> 2) - 2;
        bar_sync(2, 384);
        fetch_img<8, 384>(sm + SM_Q, g_act[*stag & 1] + 2 * 1536, tid - 128);
        mbar_arrive(sb + B_Q);
        float acc[6][16];
#pragma unroll
        for (int b = 0; b < 6; b++)
#pragma unroll
            for (int i = 0; i < 16; i++) acc[b][i] = 0.f;
        const float2* alpha = reinterpret_cast<const float2*>(sm + SM_ALPHA);
        const uint32_t lp = dlB(sb + SM_P);
        for (int k = 0, go = 1; go; go = more_units(sb, k), k++) {
            int sl = 0;
#pragma unroll
            for (int tb = 0; tb < 2; tb++) {
                const int s0 = slot; if (++slot == NG) { slot = 0; ph ^= 1; }
                const int s1 = slot; if (++slot == NG) { slot = 0; ph ^= 1; }
                if (tb == 0) { sl = slot; if (++slot == NG) { slot = 0; ph ^= 1; } }
                const uint32_t gh = dlA(sb + SM_RING + (hf ? s1 : s0) * GB), gl = dlA(sb + SM_RING + sl * GB + hf * 12288), lb = lp + tb * 256;
                mbar_wait(sb + B_PFULL + 8 * tb, k & 1);
#pragma unroll
                for (int n = 0; n < 4; n++) {
                    const float2 a = alpha[tb * 16 + 4 * n + t];
#pragma unroll
                    for (int b = 0; b < 6; b++) { acc[b][4 * n] *= a.x; acc[b][4 * n + 1] *= a.y; acc[b][4 * n + 2] *= a.x; acc[b][4 * n + 3] *= a.y; }
                }
                wg_fence();
                if (tb == 1) wgpv<2, 4096, 8192>(acc[3], acc[4], acc[5], gl, lp);
                wgpv<4, 8192, 0>(acc[0], acc[1], acc[2], gh, lb);
                wg_commit(); wg_wait0();
#pragma unroll
                for (int b = 0; b < 6; b++) pin(acc[b]);
                if (lane == 0) {
                    if (tb == 1) mbar_arrive(sb + B_EMPTY + 8 * sl);
                    mbar_arrive(sb + B_EMPTY + 8 * s0); mbar_arrive(sb + B_EMPTY + 8 * s1);
                    mbar_arrive(sb + B_PEMPTY + 8 * tb);
                }
            }
        }
        if (tid == 256) TS(4);
        uint2* ub = reinterpret_cast<uint2*>(g_U) + (size_t)cta * 128 * 52 + (t >> 1) * 16 * 52 + g * 2 + (t & 1);
        const uint32_t par = *stag & 1;
#pragma unroll
        for (int b = 0; b < 6; b++) {
            const int si = 4 * ((b < 3 ? b : b + 3) + 3 * hf) + w, cs = si / 3, sub = si - 3 * cs;
#pragma unroll
            for (int n = 0; n < 4; n++) {
                const float x0 = __uint_as_float((__float_as_uint(acc[b][4 * n]) + 0x10000u) & 0xfffe0000u);
                ub[(2 * n * 16 + cs) * 52 + sub * 16] = make_uint2(pack2(x0, acc[b][4 * n + 1]) | par, pack2(acc[b][4 * n + 2], acc[b][4 * n + 3]));
            }
        }
        bar_sync(3, 384);
        if (tid == 256) { mbar_wait(sb + B_Z, 0); st_rlx(&g_done[cta], *stag); TS(5); }
    }
    tail(p, *stag, sm, sb, slot, ph);
}

typedef CUresult (*EncFn)(CUtensorMap*, CUtensorMapDataType, cuuint32_t, void*, const cuuint64_t*, const cuuint64_t*, const cuuint32_t*,
                          const cuuint32_t*, CUtensorMapInterleave, CUtensorMapSwizzle, CUtensorMapL2promotion, CUtensorMapFloatOOBfill);
void enc(EncFn fn, CUtensorMap* m, const void* base, int rank, const cuuint64_t* dims, const cuuint64_t* str, const cuuint32_t* box,
         CUtensorMapSwizzle sw = CU_TENSOR_MAP_SWIZZLE_128B) {
    const cuuint32_t es[5] = {1, 1, 1, 1, 1};
    fn(m, CU_TENSOR_MAP_DATA_TYPE_BFLOAT16, rank, const_cast<void*>(base), dims, str, box, es, CU_TENSOR_MAP_INTERLEAVE_NONE,
       sw, CU_TENSOR_MAP_L2_PROMOTION_L2_256B, CU_TENSOR_MAP_FLOAT_OOB_FILL_NONE);
}
}

extern "C" void kernel_launch(void* const* d_in, const int* in_sizes, int n_in, void* d_out, int out_size) {
    static EncFn fn = nullptr;
    if (!fn) {
        cudaDriverEntryPointQueryResult qr;
        cudaGetDriverEntryPoint("cuTensorMapEncodeTiled", reinterpret_cast<void**>(&fn), cudaEnableDefault, &qr);
        cudaFuncSetAttribute(detr_kernel, cudaFuncAttributeMaxDynamicSharedMemorySize, SM_TOTAL);
    }
    Params p;
    p.q = (const bf16*)d_in[0]; p.fhi = (const bf16*)d_in[1]; p.flo = (const bf16*)d_in[2];
    p.lat_hi = (const bf16*)d_in[3]; p.lat_lo = (const bf16*)d_in[4];
    p.wkv = (const bf16*)d_in[6]; p.wo = (const bf16*)d_in[7]; p.w1 = (const bf16*)d_in[8]; p.w2 = (const bf16*)d_in[9];
    p.out = (bf16*)d_out;
    CUtensorMap mHi, mLo, mWq, mWk, mLh, mLl, mW1, mW2;
    { const cuuint64_t d[5] = {64, 8, 2, 9216, 6}, s[4] = {1536, 768, 12288, 128}; const cuuint32_t b[5] = {64, 8, 2, 4, 3}; enc(fn, &mHi, p.fhi, 5, d, s, b); }
    { const cuuint64_t d[3] = {64, 36864, 6}, s[2] = {768, 128}; const cuuint32_t b[3] = {64, 32, 6}; enc(fn, &mLo, p.flo, 3, d, s, b); }
    { const cuuint64_t d[2] = {384, 384}, s[1] = {768}; const cuuint32_t b[2] = {64, 192}; enc(fn, &mWq, d_in[5], 2, d, s, b); }
    { const cuuint64_t d[3] = {64, 384, 6}, s[2] = {1536, 128}; const cuuint32_t b[3] = {64, 64, 3}; enc(fn, &mWk, p.wkv, 3, d, s, b); }
    { const cuuint64_t d[3] = {64, 384, 6}, s[2] = {768, 128}; const cuuint32_t b[3] = {64, 64, 3};
      enc(fn, &mLh, p.lat_hi, 3, d, s, b); enc(fn, &mLl, p.lat_lo, 3, d, s, b); }
    { const cuuint64_t d[2] = {1536, 384}, s[1] = {3072}; const cuuint32_t b[2] = {64, 192}; enc(fn, &mW1, p.w1, 2, d, s, b); }
    { const cuuint64_t d[2] = {384, 1536}, s[1] = {768}; const cuuint32_t b[2] = {16, 256}; enc(fn, &mW2, p.w2, 2, d, s, b, CU_TENSOR_MAP_SWIZZLE_NONE); }
    detr_kernel<<<NCTA, 512, SM_TOTAL, cudaStreamPerThread>>>(mHi, mLo, mWq, mWk, mLh, mLl, mW1, mW2, p);
}
```

```cpp
#include <cuda_runtime.h>
#include <cuda_bf16.h>
#include <cuda.h>
#include <stdint.h>

namespace {
typedef __nv_bfloat16 bf16;
constexpr int C = 384, FF = 1536;
constexpr int NCTA = 128, NU = 1152;
constexpr int NG = 7, GB = 24576;
constexpr int NPRO = 24;
#define PACE 1
#define PFG 2
#define WCE 1
#define WCS 0
#define WCB 300
#define ACQF 0
#define PREP 1
#define FIX1 0
#define FIX2 0
#define WIN 3
#define WINK 7
#define WIN2 2
#define WINK2 7
#define FIX3 0
#define FIX4 1
#define PFK 3
#define NSTAT 4
#define CLAIM_J 3
#define STATIC 0
constexpr uint32_t SM_Q = 0, SM_RING = 49152, SM_P = SM_RING + NG * GB, SM_PD = SM_P + 8192,
                   SM_WMAX = SM_PD + 2048, SM_ALPHA = SM_WMAX + 512, SM_BAR = SM_ALPHA + 256,
                   SM_TOTAL = SM_BAR + 256;
static_assert(SM_TOTAL <= 232448, "smem");
constexpr uint32_t B_FULL = SM_BAR, B_EMPTY = B_FULL + 8 * NG, B_PFULL = B_EMPTY + 8 * NG,
                   B_PEMPTY = B_PFULL + 16, B_Q = B_PEMPTY + 16, B_Z = B_Q + 8, S_MORE = B_Z + 8, S_TAG = S_MORE + 16;
constexpr uint32_t SPIN_LIMIT = 1u << 22;

__device__ uint32_t g_epoch;
__device__ uint32_t g_cntW[2 * 32];
__device__ uint32_t g_next;
__device__ __align__(128) uint32_t g_flagP[32];
__device__ __align__(128) uint32_t g_done[NCTA];
__device__ uint4 g_act[2][4 * 1536];
__device__ __align__(16) uint32_t g_WvoT[C * C / 2];
__device__ uint4 g_WcF[16 * 72 * 32];
__device__ uint4 g_U[NCTA * 128 * 26];
constexpr int X_HP = 0, X_H = 16 * 32 * C, X_HN = X_H + 32 * C, X_A = X_HN + 32 * C / 2, X_END = X_A + 32 * FF / 2;
__device__ __align__(16) uint32_t g_x[X_END];
#define TS(i)

struct Params { const bf16 *q, *fhi, *flo, *lat_hi, *lat_lo, *wkv, *wo, *w1, *w2; bf16* out; };

__device__ __forceinline__ void mbar_init(uint32_t b, uint32_t n) { asm volatile("mbarrier.init.shared::cta.b64 [%0], %1;" ::"r"(b), "r"(n) : "memory"); }
__device__ __forceinline__ void mbar_arrive(uint32_t b) { asm volatile("mbarrier.arrive.shared::cta.b64 _, [%0];" ::"r"(b) : "memory"); }
__device__ __forceinline__ void mbar_expect(uint32_t b, uint32_t n) { asm volatile("mbarrier.arrive.expect_tx.shared::cta.b64 _, [%0], %1;" ::"r"(b), "r"(n) : "memory"); }
__device__ __forceinline__ void mbar_wait(uint32_t b, uint32_t par) {
    uint32_t ok, n = 0;
    do {
        asm volatile("{\n.reg .pred p;\nmbarrier.try_wait.parity.shared::cta.b64 p, [%1], %2;\nselp.u32 %0, 1, 0, p;\n}"
                     : "=r"(ok) : "r"(b), "r"(par) : "memory");
        if (++n > SPIN_LIMIT) __trap();
    } while (!ok);
}
__device__ __forceinline__ bool mbar_test(uint32_t b, uint32_t par) {
    uint32_t ok;
    asm volatile("{\n.reg .pred p;\nmbarrier.test_wait.parity.shared::cta.b64 p, [%1], %2;\nselp.u32 %0, 1, 0, p;\n}"
                 : "=r"(ok) : "r"(b), "r"(par) : "memory");
    return ok;
}
__device__ __forceinline__ void bar_sync(int id, int n) { asm volatile("bar.sync %0, %1;" ::"r"(id), "r"(n) : "memory"); }
__device__ __forceinline__ void fence_async() { asm volatile("fence.proxy.async;" ::: "memory"); }
__device__ __forceinline__ void fence_async_s() { asm volatile("fence.proxy.async.shared::cta;" ::: "memory"); }
__device__ __forceinline__ void fence_gpu() { asm volatile("fence.acq_rel.gpu;" ::: "memory"); }
__device__ __forceinline__ uint32_t ld_acq(const uint32_t* p) { uint32_t v; asm volatile("ld.acquire.gpu.global.u32 %0, [%1];" : "=r"(v) : "l"(p) : "memory"); return v; }
__device__ __forceinline__ uint32_t ld_rlx(const uint32_t* p) { uint32_t v; asm volatile("ld.relaxed.gpu.global.u32 %0, [%1];" : "=r"(v) : "l"(p) : "memory"); return v; }
__device__ __forceinline__ void st_rlx(uint32_t* p, uint32_t v) { asm volatile("st.relaxed.gpu.global.u32 [%0], %1;" ::"l"(p), "r"(v) : "memory"); }
__device__ __forceinline__ void poll_ge(const uint32_t* p, uint32_t tgt) {
    uint32_t n = 0;
    while ((int)(ld_acq(p) - tgt) < 0) { if (++n > SPIN_LIMIT) __trap(); }
}
__device__ __forceinline__ uint4 ld_rlx4(const void* p) {
    uint4 v; asm volatile("ld.relaxed.gpu.global.v4.u32 {%0, %1, %2, %3}, [%4];" : "=r"(v.x), "=r"(v.y), "=r"(v.z), "=r"(v.w) : "l"(p) : "memory");
    return v;
}
__device__ __forceinline__ bool nz4(const uint4& v) { return v.x && v.y && v.z && v.w; }
__device__ __forceinline__ uint4 poll4(const void* p) {
    uint4 v = ld_rlx4(p); uint32_t n = 0;
    while (!nz4(v)) { v = ld_rlx4(p); if (++n > SPIN_LIMIT) __trap(); }
    return v;
}
template <int N, int NT>
__device__ __forceinline__ void fetch_img(uint8_t* dst, const uint4* src, int i0) {
    uint4 v[N]; uint32_t n = 0; bool ok;
    if (FIX2) {
#pragma unroll
        for (int i = 0; i < N; i++) v[i] = make_uint4(0, 0, 0, 0);
    }
    do {
        ok = true;
#pragma unroll
        for (int i = 0; i < N; i++) if (!FIX2 || !nz4(v[i])) v[i] = ld_rlx4(src + i0 + i * NT);
#pragma unroll
        for (int i = 0; i < N; i++) ok = ok && nz4(v[i]);
        if (++n > SPIN_LIMIT) __trap();
    } while (!ok);
#pragma unroll
    for (int i = 0; i < N; i++) reinterpret_cast<uint4*>(dst)[i0 + i * NT] = make_uint4(~v[i].x, ~v[i].y, ~v[i].z, ~v[i].w);
    fence_async_s();
}
__device__ __forceinline__ void gate_img(int f0, int nblk, int lane, uint32_t first, uint32_t tag) {
    if (lane >= f0 && lane < f0 + nblk) { uint32_t n = 0; while (first != tag) { first = ld_rlx(&g_flagP[lane]); if (++n > SPIN_LIMIT) __trap(); } }
    __syncwarp();
}
__device__ __forceinline__ bool more_units(uint32_t sb, int k) {
    uint32_t v, n = 0;
    do {
        asm volatile("ld.volatile.shared.u32 %0, [%1];" : "=r"(v) : "r"(sb + S_MORE + 4 * (k & 3)) : "memory");
        if (++n > SPIN_LIMIT) __trap();
    } while ((int)(v >> 1) != k + 1);
    return v & 1;
}
__device__ __forceinline__ uint32_t pack2(float lo, float hi) { uint32_t r; asm("cvt.rn.bf16x2.f32 %0, %1, %2;" : "=r"(r) : "f"(hi), "f"(lo)); return r; }
__device__ __forceinline__ float bflo(uint32_t v) { return __uint_as_float(v << 16); }
__device__ __forceinline__ float bfhi(uint32_t v) { return __uint_as_float(v & 0xffff0000u); }
__device__ __forceinline__ float ex2(float x) { float r; asm("ex2.approx.ftz.f32 %0, %1;" : "=f"(r) : "f"(x)); return r; }
__device__ __forceinline__ uint32_t movtrans(uint32_t v) { uint32_t r; asm volatile("movmatrix.sync.aligned.m8n8.trans.b16 %0, %1;" : "=r"(r) : "r"(v)); return r; }
__device__ __forceinline__ void stsm4t(uint32_t a, uint32_t r0, uint32_t r1, uint32_t r2, uint32_t r3) {
    asm volatile("stmatrix.sync.aligned.m8n8.x4.trans.shared.b16 [%0], {%1, %2, %3, %4};" ::"r"(a), "r"(r0), "r"(r1), "r"(r2), "r"(r3) : "memory");
}
__device__ __forceinline__ uint4 ldsm4t(uint32_t a) {
    uint4 r; asm volatile("ldmatrix.sync.aligned.m8n8.x4.trans.shared.b16 {%0, %1, %2, %3}, [%4];" : "=r"(r.x), "=r"(r.y), "=r"(r.z), "=r"(r.w) : "r"(a) : "memory");
    return r;
}
__device__ __forceinline__ void mma16816(float (&d)[4], const uint32_t a0, const uint32_t a1, const uint32_t a2, const uint32_t a3, uint32_t b0, uint32_t b1) {
    asm volatile("mma.sync.aligned.m16n8k16.row.col.f32.bf16.bf16.f32 {%0,%1,%2,%3}, {%4,%5,%6,%7}, {%8,%9}, {%0,%1,%2,%3};"
                 : "+f"(d[0]), "+f"(d[1]), "+f"(d[2]), "+f"(d[3]) : "r"(a0), "r"(a1), "r"(a2), "r"(a3), "r"(b0), "r"(b1));
}
__device__ __forceinline__ uint32_t dlA(uint32_t a) { return (a >> 4) | (64u << 16); }
__device__ __forceinline__ uint32_t dlB(uint32_t a) { return (a >> 4) | (32u << 16); }
template <int TA, int SBO, int OA, int OB, int SC>
__device__ __forceinline__ void wgmma32(float (&d)[16], uint32_t la, uint32_t lb) {
    asm volatile("{\n.reg .pred p;\n.reg .b32 x, y;\n.reg .b64 da, db;\nsetp.ne.b32 p, %18, 0;\n"
                 "add.u32 x, %16, %20;\nadd.u32 y, %17, %21;\nmov.b64 da, {x, %22};\nmov.b64 db, {y, 8};\n"
                 "wgmma.mma_async.sync.aligned.m64n32k16.f32.bf16.bf16 "
                 "{%0,%1,%2,%3,%4,%5,%6,%7,%8,%9,%10,%11,%12,%13,%14,%15}, da, db, p, 1, 1, %19, 0;\n}"
                 : "+f"(d[0]), "+f"(d[1]), "+f"(d[2]), "+f"(d[3]), "+f"(d[4]), "+f"(d[5]), "+f"(d[6]), "+f"(d[7]),
                   "+f"(d[8]), "+f"(d[9]), "+f"(d[10]), "+f"(d[11]), "+f"(d[12]), "+f"(d[13]), "+f"(d[14]), "+f"(d[15])
                 : "r"(la), "r"(lb), "n"(SC), "n"(TA), "n"(OA >> 4), "n"(OB >> 4), "n"((SBO >> 4) | 0x40000000));
}
template <int TA, int SBO, int N, int PER, int CH, int ST, int OA, int OB, int SC0, int I = 0>
__device__ __forceinline__ void wgchain(float (&d)[16], uint32_t la, uint32_t lb) {
    if constexpr (I < N) {
        wgmma32<TA, SBO, OA + (I / PER) * CH + (I % PER) * ST, OB + I * 1024, (I == 0 ? SC0 : 1)>(d, la, lb);
        wgchain<TA, SBO, N, PER, CH, ST, OA, OB, SC0, I + 1>(d, la, lb);
    }
}
template <int TA, int SBO, int N, int PER, int CH, int ST, int OA, int OB, int SC0, int I = 0>
__device__ __forceinline__ void wgchain2(float (&d)[16], float (&e)[16], uint32_t la, uint32_t lb) {
    if constexpr (I < N) {
        wgmma32<TA, SBO, OA + (I / PER) * CH + (I % PER) * ST, OB + I * 1024, (I < 2 ? SC0 : 1)>(d, la, lb);
        wgchain2<TA, SBO, N, PER, CH, ST, OA, OB, SC0, I + 1>(e, d, la, lb);
    }
}
template <int N, int CH, int OB, int I = 0>
__device__ __forceinline__ void wgpv(float (&a)[16], float (&b)[16], float (&c)[16], uint32_t la, uint32_t lb) {
    if constexpr (I < N) {
        wgmma32<1, 1024, I * 2048, OB + I * 1024, 1>(a, la, lb);
        wgmma32<1, 1024, CH + I * 2048, OB + I * 1024, 1>(b, la, lb);
        wgmma32<1, 1024, 2 * CH + I * 2048, OB + I * 1024, 1>(c, la, lb);
        wgpv<N, CH, OB, I + 1>(a, b, c, la, lb);
    }
}
__device__ __forceinline__ void wg_fence() { asm volatile("wgmma.fence.sync.aligned;" ::: "memory"); }
__device__ __forceinline__ void wg_commit() { asm volatile("wgmma.commit_group.sync.aligned;" ::: "memory"); }
__device__ __forceinline__ void wg_wait0() { asm volatile("wgmma.wait_group.sync.aligned 0;" ::: "memory"); }
__device__ __forceinline__ void pin(float (&d)[16]) {
#pragma unroll
    for (int i = 0; i < 16; i++) asm volatile("" : "+f"(d[i])::"memory");
}
__device__ __forceinline__ void tma2(uint32_t dst, const CUtensorMap* m, int c0, int c1, uint32_t bar) {
    asm volatile("cp.async.bulk.tensor.2d.shared::cluster.global.mbarrier::complete_tx::bytes [%0], [%1, {%3, %4}], [%2];"
                 ::"r"(dst), "l"(m), "r"(bar), "r"(c0), "r"(c1) : "memory");
}
__device__ __forceinline__ void tma3(uint32_t dst, const CUtensorMap* m, int c1, int c2, uint32_t bar, uint64_t pol) {
    asm volatile("cp.async.bulk.tensor.3d.shared::cluster.global.mbarrier::complete_tx::bytes.L2::cache_hint [%0], [%1, {%3, %4, %5}], [%2], %6;"
                 ::"r"(dst), "l"(m), "r"(bar), "r"(0), "r"(c1), "r"(c2), "l"(pol) : "memory");
}
__device__ __forceinline__ void tma5(uint32_t dst, const CUtensorMap* m, int c3, int c4, uint32_t bar, uint64_t pol) {
    asm volatile("cp.async.bulk.tensor.5d.shared::cluster.global.mbarrier::complete_tx::bytes.L2::cache_hint [%0], [%1, {%3, %3, %3, %4, %5}], [%2], %6;"
                 ::"r"(dst), "l"(m), "r"(bar), "r"(0), "r"(c3), "r"(c4), "l"(pol) : "memory");
}
__device__ __forceinline__ void bulk_g2s(uint32_t dst, const void* src, uint32_t n, uint32_t bar) {
    asm volatile("cp.async.bulk.shared::cluster.global.mbarrier::complete_tx::bytes [%0], [%1], %2, [%3];" ::"r"(dst), "l"(src), "r"(n), "r"(bar) : "memory");
}
__device__ __forceinline__ void l2_prefetch(const void* src, uint32_t n) { asm volatile("cp.async.bulk.prefetch.L2.global [%0], %1;" ::"l"(src), "r"(n) : "memory"); }
__device__ __forceinline__ float wsum(float v) {
#pragma unroll
    for (int o = 16; o; o >>= 1) v += __shfl_xor_sync(~0u, v, o);
    return v;
}

__device__ __forceinline__ void tail(const Params& p, uint32_t tag, uint8_t* sm, uint32_t sb, int slot, int ph) {
    const int tid = threadIdx.x - 128, wid = tid >> 5, lane = tid & 31, g = lane >> 2, t = lane & 3, cta = blockIdx.x;
    const int rg = cta >> 4, cs = cta & 15;
    float* red = reinterpret_cast<float*>(sm + SM_RING + (slot ? slot - 1 : NG - 1) * GB);
    float4* redW = reinterpret_cast<float4*>(red + 3072);
    float4* redM = redW + 128;
    bf16* Us = reinterpret_cast<bf16*>(redM + 8);
    float* rs = reinterpret_cast<float*>(Us + 8 * 56);
    float* red2 = reinterpret_cast<float*>(sm + SM_Q + 1024);
    auto frag = [&](int gi) -> const uint4* {
        const int sl = slot + gi >= NG ? slot + gi - NG : slot + gi;
        mbar_wait(sb + B_FULL + 8 * sl, slot + gi >= NG ? ph ^ 1 : ph);
        return reinterpret_cast<const uint4*>(sm + SM_RING + sl * GB);
    };
    volatile uint32_t* msk = reinterpret_cast<volatile uint32_t*>(sm + SM_Q + 512);
    auto poll_done = [&]() -> bool {
        const uint4 f = ld_rlx4(&g_done[4 * lane]);
        const uint32_t b0 = __ballot_sync(~0u, f.x == tag), b1 = __ballot_sync(~0u, f.y == tag);
        const uint32_t b2 = __ballot_sync(~0u, f.z == tag), b3 = __ballot_sync(~0u, f.w == tag);
        if (lane < 4) msk[lane] = lane == 0 ? b0 : lane == 1 ? b1 : lane == 2 ? b2 : b3;
        __syncwarp();
        return (b0 & b1 & b2 & b3) != ~0u;
    };
    if (PREP) { if (wid == 0) poll_done(); } else if (tid < 4) msk[tid] = 0;
    bar_sync(2, 384);
    {
        const int pg = tid / 24, u = tid - pg * 24;
        const uint4* src = &g_U[(pg * 128 + cta) * 26] + u;
        const uint4* ml = &g_U[((tid & 127) * 128 + cta) * 26 + 24];
        const uint32_t par = tag & 1;
        uint4 v[8], m, l; uint32_t n = 0;
        {
            uint32_t todo = tid < 128 ? 0x11111113u : 0x11111111u;
            bool more = wid == 0;
            do {
                if (more && (!PREP || n)) more = poll_done();
                const uint32_t go = todo & (((msk[pg & 3] >> (pg >> 2)) & 0x11111111u) | (((msk[tid & 3] >> ((tid >> 2) & 31)) & 1) << 1));
#pragma unroll
                for (int i = 0; i < 8; i++) if (go >> (4 * i) & 1) v[i] = ld_rlx4(src + i * (16 * 128 * 26));
                if (go & 2) { m = ld_rlx4(ml); l = ld_rlx4(ml + 1); }
                todo &= ~go;
                if (++n > SPIN_LIMIT) __trap();
            } while (__any_sync(~0u, todo != 0) || more);
            if (ACQF && tid == 0) fence_gpu();
            if (tid == 0) TS(6);
        }
#define FM(x) __uint_as_float((x) & ~1u)
#define BAD4(v) ((((v).x ^ par) | ((v).y ^ par) | ((v).z ^ par) | ((v).w ^ par)) & 1)
        float4 mm, ll;
        if (tid < 128) {
            while (BAD4(m) | BAD4(l)) { m = ld_rlx4(ml); l = ld_rlx4(ml + 1); if (++n > SPIN_LIMIT) __trap(); }
            mm = make_float4(FM(m.x), FM(m.y), FM(m.z), FM(m.w)); ll = make_float4(FM(l.x), FM(l.y), FM(l.z), FM(l.w));
            float4 M = mm;
#pragma unroll
            for (int o = 16; o; o >>= 1) {
                M.x = fmaxf(M.x, __shfl_xor_sync(~0u, M.x, o)); M.y = fmaxf(M.y, __shfl_xor_sync(~0u, M.y, o));
                M.z = fmaxf(M.z, __shfl_xor_sync(~0u, M.z, o)); M.w = fmaxf(M.w, __shfl_xor_sync(~0u, M.w, o));
            }
            if (lane == 0) redM[wid] = M;
            bar_sync(1, 128);
            const float4 a = redM[0], b = redM[1], c = redM[2], d = redM[3];
            const float4 w4 = make_float4(ex2(mm.x - fmaxf(fmaxf(a.x, b.x), fmaxf(c.x, d.x))), ex2(mm.y - fmaxf(fmaxf(a.y, b.y), fmaxf(c.y, d.y))),
                                          ex2(mm.z - fmaxf(fmaxf(a.z, b.z), fmaxf(c.z, d.z))), ex2(mm.w - fmaxf(fmaxf(a.w, b.w), fmaxf(c.w, d.w))));
            redW[tid] = w4;
            const float4 L = make_float4(wsum(w4.x * ll.x), wsum(w4.y * ll.y), wsum(w4.z * ll.z), wsum(w4.w * ll.w));
            if (lane == 0) redM[4 + wid] = L;
        }
#pragma unroll
        for (int i = 0; i < 8; i++)
            while (((v[i].x ^ par) | (v[i].z ^ par)) & 1) { v[i] = ld_rlx4(src + i * (16 * 128 * 26)); if (++n > SPIN_LIMIT) __trap(); }
        bar_sync(2, 384);
        if (tid == 0) TS(12);
        float a[8] = {0, 0, 0, 0, 0, 0, 0, 0};
#pragma unroll
        for (int i = 0; i < 8; i++) {
            const float4 w = redW[pg + 16 * i];
            a[0] += w.x * bflo(v[i].x & ~1u); a[1] += w.y * bfhi(v[i].x); a[2] += w.x * bflo(v[i].y); a[3] += w.y * bfhi(v[i].y);
            a[4] += w.z * bflo(v[i].z & ~1u); a[5] += w.w * bfhi(v[i].z); a[6] += w.z * bflo(v[i].w); a[7] += w.w * bfhi(v[i].w);
        }
        float4* dst = reinterpret_cast<float4*>(red + pg * 192 + u * 8);
        dst[0] = make_float4(a[0], a[1], a[2], a[3]); dst[1] = make_float4(a[4], a[5], a[6], a[7]);
        if (tid < 112) reinterpret_cast<uint32_t*>(Us + 4 * 56)[tid] = 0;
        const uint4* wcp = frag(wid >= 8) + (wid & 7) * 192 + lane;
        uint4 wc[6];
#pragma unroll
        for (int i = 0; i < 6; i++) wc[i] = wcp[32 * i];
        bar_sync(2, 384);
        if (tid < 192) {
            const int j = tid & 7, uu = tid >> 3, ql = 2 * (j >> 2) + (j & 1), ch = 16 * (uu >> 3) + (uu & 7) + 8 * ((j >> 1) & 1);
            const float* pl = reinterpret_cast<const float*>(redM + 4) + ql;
            float num = 0;
#pragma unroll
            for (int i = 0; i < 16; i++) num += red[i * 192 + tid];
            Us[ql * 56 + ch] = __float2bfloat16(__fdividef(num, (pl[0] + pl[4]) + (pl[8] + pl[12])));
        }
        bar_sync(2, 384);
        const uint32_t* ub = reinterpret_cast<const uint32_t*>(Us + g * 56) + t;
#pragma unroll
        for (int j = 0; j < 2; j++) {
            float d[4] = {0, 0, 0, 0};
#pragma unroll
            for (int ks = 0; ks < 3; ks++) mma16816(d, wc[3 * j + ks].x, wc[3 * j + ks].y, wc[3 * j + ks].z, wc[3 * j + ks].w, ub[8 * ks], ub[8 * ks + 4]);
            if (t < 2) {
                uint32_t* o = &g_x[X_HP + (cs * 32 + 4 * rg + 2 * t) * C + 16 * (2 * wid + j) + g];
                st_rlx(o, ~__float_as_uint(d[0])); st_rlx(o + C, ~__float_as_uint(d[1]));
                st_rlx(o + 8, ~__float_as_uint(d[2])); st_rlx(o + C + 8, ~__float_as_uint(d[3]));
            }
        }
        if (tid == 0) TS(7);
    }
    if (cta >= 96) {
        const int q = cta - 96;
        const float qv = __bfloat162float(p.q[q * C + tid]);
        uint32_t v[16] = {}, n = 0; bool ok;
        do {
            ok = true;
#pragma unroll
            for (int i = 0; i < 16; i++) if (!FIX3 || !v[i]) v[i] = ld_rlx(&g_x[X_HP + (i * 32 + q) * C + tid]);
#pragma unroll
            for (int i = 0; i < 16; i++) ok = ok && v[i];
            if (++n > SPIN_LIMIT) __trap();
        } while (!ok);
        float h = qv;
#pragma unroll
        for (int i = 0; i < 16; i++) h += __uint_as_float(~v[i]);
        st_rlx(&g_x[X_H + q * C + tid], ~__float_as_uint(h));
        const float mw = wsum(h) * (1.0f / 32), qw = wsum((h - mw) * (h - mw));
        if (lane == 0) { rs[wid] = mw; rs[16 + wid] = qw; }
        bar_sync(2, 384);
        float s = 0, s2 = 0;
#pragma unroll
        for (int i = 0; i < 12; i++) s += rs[i];
        s *= 1.0f / 12;
#pragma unroll
        for (int i = 0; i < 12; i++) s2 += rs[16 + i] + 32.0f * (rs[i] - s) * (rs[i] - s);
        const float dv = h - s;
        const float hn = dv * rsqrtf(s2 * (1.0f / C) + 1e-5f);
        const float hn1 = __shfl_down_sync(~0u, hn, 1);
        if (!(lane & 1)) st_rlx(&g_x[X_HN + q * (C / 2) + (tid >> 1)], ~pack2(hn, hn1));
        if (tid == 0) TS(8);
        return;
    }
    const int r4 = cta / 24, c24 = cta - r4 * 24;
    uint4 A1[8], A2[8];
    {
        const int kr = 8 * ((lane & 7) >> 1) + (lane & 1) + 2 * (lane >> 4), hi = (lane >> 3) & 1;
        const uint32_t f1 = (uint32_t)__cvta_generic_to_shared(frag(2 + (wid >= 6))) + (32 * (wid % 6) + kr) * 128;
        const uint32_t f2 = (uint32_t)__cvta_generic_to_shared(frag(4 + (wid >= 6))) + (128 * (wid % 6) + kr) * 32 + hi * 16;
#pragma unroll
        for (int s = 0; s < 8; s++) {
            A1[s] = ldsm4t(f1 + (s & 1) * 512 + (((2 * (s >> 1) + hi) ^ ((kr + 4 * (s & 1)) & 7)) << 4));
            A2[s] = ldsm4t(f2 + (32 * (s >> 1) + 4 * (s & 1)) * 32);
        }
    }
    {
        const uint4 b = poll4(&g_x[X_HN + (8 * r4 + g) * (C / 2) + 16 * wid + 4 * t]);
        __syncwarp();
        if (tid == 0) TS(8);
#pragma unroll
        for (int mt = 0; mt < 4; mt++) {
            float d[4] = {0, 0, 0, 0};
            mma16816(d, A1[2 * mt].x, A1[2 * mt].y, A1[2 * mt].z, A1[2 * mt].w, ~b.x, ~b.y);
            mma16816(d, A1[2 * mt + 1].x, A1[2 * mt + 1].y, A1[2 * mt + 1].z, A1[2 * mt + 1].w, ~b.z, ~b.w);
            float* o = red2 + (wid * 8 + 2 * t) * 68 + 16 * mt + g;
            o[0] = d[0]; o[68] = d[1]; o[8] = d[2]; o[76] = d[3];
        }
        bar_sync(2, 384);
        if (tid < 256) {
            const float2* r2 = reinterpret_cast<const float2*>(red2 + wid * 68) + lane;
            float x = 0, y = 0;
#pragma unroll
            for (int i = 0; i < 12; i++) { const float2 z = r2[i * 272]; x += z.x; y += z.y; }
            const float ex = __expf(-1.5957691216057308f * (x + 0.044715f * x * x * x)), ey = __expf(-1.5957691216057308f * (y + 0.044715f * y * y * y));
            st_rlx(&g_x[X_A + (8 * r4 + wid) * (FF / 2) + 32 * c24 + lane], ~pack2(x / (1.0f + ex), y / (1.0f + ey)));
        }
        if (tid == 0) TS(9);
    }
    {
        const int oq = 8 * r4 + (tid >> 3), oc = 16 * c24 + 2 * (tid & 7);
        const uint32_t* src = &g_x[X_A + (8 * r4 + g) * (FF / 2) + 64 * wid + 4 * t];
        uint4 b[4];
        uint32_t h0 = 1, h1 = 1;
        if (FIX4) {
            if (tid < 64) { h0 = ld_rlx(&g_x[X_H + oq * C + oc]); h1 = ld_rlx(&g_x[X_H + oq * C + oc + 1]); }
            uint32_t n = 0;
#pragma unroll
            for (int j = 0; j < 4; j++) b[j] = make_uint4(0, 0, 0, 0);
            do {
#pragma unroll
                for (int j = 0; j < 4; j++) if (!nz4(b[j])) b[j] = ld_rlx4(src + 16 * j);
                if (++n > SPIN_LIMIT) __trap();
            } while (!(nz4(b[0]) && nz4(b[1]) && nz4(b[2]) && nz4(b[3])));
        } else {
        b[0] = poll4(src);
#pragma unroll
        for (int j = 1; j < 4; j++) b[j] = ld_rlx4(src + 16 * j);
        if (tid < 64) { h0 = ld_rlx(&g_x[X_H + oq * C + oc]); h1 = ld_rlx(&g_x[X_H + oq * C + oc + 1]); }
#pragma unroll
        for (int j = 1; j < 4; j++) if (!nz4(b[j])) b[j] = poll4(src + 16 * j);
        }
        __syncwarp();
        if (tid == 0) TS(10);
        float d[4] = {0, 0, 0, 0}, e[4] = {0, 0, 0, 0};
#pragma unroll
        for (int j = 0; j < 4; j++) {
            mma16816(d, A2[2 * j].x, A2[2 * j].y, A2[2 * j].z, A2[2 * j].w, ~b[j].x, ~b[j].y);
            mma16816(e, A2[2 * j + 1].x, A2[2 * j + 1].y, A2[2 * j + 1].z, A2[2 * j + 1].w, ~b[j].z, ~b[j].w);
        }
        float* o = red + (wid * 8 + 2 * t) * 20 + g;
        o[0] = d[0] + e[0]; o[20] = d[1] + e[1]; o[8] = d[2] + e[2]; o[28] = d[3] + e[3];
        bar_sync(2, 384);
        if (tid < 64) {
            uint32_t n = 0;
            while (!h0 || !h1) { h0 = ld_rlx(&g_x[X_H + oq * C + oc]); h1 = ld_rlx(&g_x[X_H + oq * C + oc + 1]); if (++n > SPIN_LIMIT) __trap(); }
            float x = __uint_as_float(~h0), y = __uint_as_float(~h1);
            const float2* r = reinterpret_cast<const float2*>(red + (tid >> 3) * 20) + (tid & 7);
#pragma unroll
            for (int i = 0; i < 12; i++) { const float2 z = r[80 * i]; x += z.x; y += z.y; }
            *reinterpret_cast<uint32_t*>(p.out + oq * C + oc) = pack2(x, y);
        }
        if (tid == 0) { if (cta == 0) { st_rlx(&g_next, 0); st_rlx(&g_epoch, tag); } TS(11); }
    }
}

__device__ __forceinline__ void wcomb(const Params& p, volatile uint32_t* stag, int hw, int lane, uint32_t sbq) {
    const int g = lane >> 2, t = lane & 3, mt = hw % 24, grp = hw / 24;
    {
        float d[4][4] = {};
        const bf16* wv = p.wkv + (size_t)(32 * grp + g) * (2 * C) + C + 8 * t;
        const uint32_t* wo = reinterpret_cast<const uint32_t*>(p.wo + (8 * (g >> 1) + (g & 1)) * C + 16 * mt) + t;
#pragma unroll 1
        for (int k3 = 0; k3 < 12; k3 += 3) {
            uint32_t a[3][8]; uint4 b[3][4];
#pragma unroll
            for (int kk = 0; kk < 3; kk++) {
#pragma unroll
                for (int i = 0; i < 8; i++) a[kk][i] = __ldg(wo + (32 * (k3 + kk) + 2 * (i >> 1)) * (C / 2) + 4 * (i & 1));
#pragma unroll
                for (int j = 0; j < 4; j++) b[kk][j] = __ldg(reinterpret_cast<const uint4*>(wv + (size_t)j * 8 * 2 * C + 32 * (k3 + kk)));
            }
#pragma unroll
            for (int kk = 0; kk < 3; kk++) {
#pragma unroll
                for (int i = 0; i < 8; i++) a[kk][i] = movtrans(a[kk][i]);
#pragma unroll
                for (int j = 0; j < 4; j++) {
                    mma16816(d[j], a[kk][0], a[kk][1], a[kk][2], a[kk][3], b[kk][j].x, b[kk][j].y);
                    mma16816(d[j], a[kk][4], a[kk][5], a[kk][6], a[kk][7], b[kk][j].z, b[kk][j].w);
                }
            }
        }
#pragma unroll
        for (int j = 0; j < 4; j++) {
            uint32_t* o = &g_WvoT[(16 * mt + g) * (C / 2) + 16 * grp + 4 * j + t];
            o[0] = pack2(d[j][0], d[j][1]); o[8 * (C / 2)] = pack2(d[j][2], d[j][3]);
        }
        __syncwarp();
        if (lane == 0) { fence_gpu(); atomicAdd(&g_cntW[0], 1u);
            if (WCS) mbar_wait(sbq, 0);
            uint32_t n = 0;
            while ((int)(ld_acq(&g_cntW[0]) - *stag * 288u) < 0) { if (WCB) __nanosleep(WCB); if (++n > SPIN_LIMIT) __trap(); }
            TS(15);
        }
        __syncwarp();
    }
    {
        float d[8][4] = {};
        const bf16* lat = (grp < 6 ? p.lat_hi + (size_t)(64 * grp) * C : p.lat_lo + (size_t)(64 * (grp - 6)) * C) + g * C + 8 * t;
        const uint4* wa = reinterpret_cast<const uint4*>(g_WvoT) + (16 * mt + g) * 48 + t;
#pragma unroll 1
        for (int k2 = 0; k2 < 12; k2 += 2) {
            uint4 a[2][2], b[2][8];
#pragma unroll
            for (int kk = 0; kk < 2; kk++) {
                a[kk][0] = __ldcg(wa + 4 * (k2 + kk)); a[kk][1] = __ldcg(wa + 8 * 48 + 4 * (k2 + kk));
#pragma unroll
                for (int j = 0; j < 8; j++) b[kk][j] = __ldg(reinterpret_cast<const uint4*>(lat + j * 8 * C + 32 * (k2 + kk)));
            }
#pragma unroll
            for (int kk = 0; kk < 2; kk++)
#pragma unroll
                for (int j = 0; j < 8; j++) {
                    mma16816(d[j], a[kk][0].x, a[kk][1].x, a[kk][0].y, a[kk][1].y, b[kk][j].x, b[kk][j].y);
                    mma16816(d[j], a[kk][0].z, a[kk][1].z, a[kk][0].w, a[kk][1].w, b[kk][j].z, b[kk][j].w);
                }
        }
#pragma unroll
        for (int j = 0; j < 4; j++)
            g_WcF[(((4 * grp + j) / 3) * 72 + mt * 3 + (4 * grp + j) % 3) * 32 + lane] = make_uint4(pack2(d[2 * j][0], d[2 * j][1]), pack2(d[2 * j][2], d[2 * j][3]),
                                                                   pack2(d[2 * j + 1][0], d[2 * j + 1][1]), pack2(d[2 * j + 1][2], d[2 * j + 1][3]));
        __syncwarp();
        fence_async();
        __syncwarp();
        if (lane == 0) { fence_gpu(); atomicAdd(&g_cntW[32], 1u); TS(13); }
    }
}

__global__ void __launch_bounds__(512, 1)
detr_kernel(const __grid_constant__ CUtensorMap tmHi, const __grid_constant__ CUtensorMap tmLo,
            const __grid_constant__ CUtensorMap tmWq, const __grid_constant__ CUtensorMap tmWk,
            const __grid_constant__ CUtensorMap tmLh, const __grid_constant__ CUtensorMap tmLl,
            const __grid_constant__ CUtensorMap tmW1, const __grid_constant__ CUtensorMap tmW2, const Params p) {
    extern __shared__ __align__(1024) uint8_t sm[];
    const uint32_t sb = (uint32_t)__cvta_generic_to_shared(sm);
    const int tid = threadIdx.x, wid = tid >> 5, lane = tid & 31, cta = blockIdx.x;
    const int g = lane >> 2, t = lane & 3, w = wid & 3;
    const int pos0 = cta < NPRO ? 2 : 0;
    const uint32_t epoch = ld_rlx(&g_epoch);
    int slot = pos0, ph = 0;
    if (tid == 0) {
        TS(0);
        if (sb & 1023) __trap();
        for (int i = 0; i < NG; i++) { mbar_init(sb + B_FULL + 8 * i, 1); mbar_init(sb + B_EMPTY + 8 * i, 8); }
        for (int i = 0; i < 2; i++) { mbar_init(sb + B_PFULL + 8 * i, 128); mbar_init(sb + B_PEMPTY + 8 * i, 8); }
        mbar_init(sb + B_Q, 384); mbar_init(sb + B_Z, 3);
        *reinterpret_cast<uint4*>(sm + S_MORE) = make_uint4(0, 0, 0, 0);
        asm volatile("fence.mbarrier_init.release.cluster;" ::: "memory");
        if (FIX1) fence_async_s(); else fence_async();
            if (cta < NPRO) {
                uint64_t poln; asm volatile("createpolicy.fractional.L2::evict_normal.b64 %0, 1.0;" : "=l"(poln));
                for (int h = 0; h < 2; h++) {
                    const uint32_t dst = sb + SM_RING + h * GB, bar = sb + B_FULL + 8 * h;
                    mbar_expect(bar, GB);
                    if (cta < 6) tma2(dst, &tmWq, 64 * cta, 192 * h, bar);
                    else if (cta < 12) tma3(dst, &tmWk, 64 * (cta - 6), 3 * h, bar, poln);
                    else if (cta < 18) tma3(dst, &tmLh, 64 * (cta - 12), 3 * h, bar, poln);
                    else tma3(dst, &tmLl, 64 * (cta - 18), 3 * h, bar, poln);
                }
            }
    }
    if (cta < 6 && (wid >> 2) == 1) {
        const int row = (tid & 127) >> 2;
        uint4 x[12];
#pragma unroll
        for (int j = 0; j < 12; j++) x[j] = __ldg(reinterpret_cast<const uint4*>(p.q + row * C) + 4 * j + t);
                float sum = 0;
#pragma unroll
                for (int j = 0; j < 12; j++) sum += ((bflo(x[j].x) + bfhi(x[j].x)) + (bflo(x[j].y) + bfhi(x[j].y))) + ((bflo(x[j].z) + bfhi(x[j].z)) + (bflo(x[j].w) + bfhi(x[j].w)));
                sum += __shfl_xor_sync(~0u, sum, 1); sum += __shfl_xor_sync(~0u, sum, 2);
                const float mean = sum * (1.0f / C);
                float var = 0;
#define SQ2(v) ((bflo(v) - mean) * (bflo(v) - mean) + (bfhi(v) - mean) * (bfhi(v) - mean))
#pragma unroll
                for (int j = 0; j < 12; j++) var += (SQ2(x[j].x) + SQ2(x[j].y)) + (SQ2(x[j].z) + SQ2(x[j].w));
                var += __shfl_xor_sync(~0u, var, 1); var += __shfl_xor_sync(~0u, var, 2);
                const float rstd = rsqrtf(var * (1.0f / C) + 1e-5f);
#define NRM(v) pack2((bflo(v) - mean) * rstd, (bfhi(v) - mean) * rstd)
#pragma unroll
                for (int j = 0; j < 12; j++)
                    *reinterpret_cast<uint4*>(sm + SM_Q + (4 * j + t) * 512 + row * 16) = make_uint4(NRM(x[j].x), NRM(x[j].y), NRM(x[j].z), NRM(x[j].w));
                fence_async_s();
    }
    __syncthreads();
    volatile uint32_t* stag = reinterpret_cast<volatile uint32_t*>(sm + S_TAG);
    if (wid) *stag = epoch + 1;

    if (wid < 4) {
        if (tid == 0) {
            uint64_t pol; asm volatile("createpolicy.fractional.L2::evict_first.b64 %0, 1.0;" : "=l"(pol));
            int cnt = pos0, U = cta, Un = NCTA + cta;
            ph = 1;
            for (int k = 0; U < NU; k++) {
                const int b0 = (U / 6) * 48 + 4 * (U % 6);
#pragma unroll 1
                for (int j = 0; j < 5; j++) {
                    if (cnt >= PACE && cnt < NG) mbar_wait(sb + B_FULL + 8 * (cnt - PACE), 0);
                    if (PFG && cnt == NG) {
                        const uint8_t* prev = nullptr;
                        for (int n = NG - pos0; n < NG - pos0 + PFG && n < 5 * NSTAT; n++) {
                            const int UU = (n / 5) * NCTA + cta, jj = n % 5, bb = (UU / 6) * 48 + 4 * (UU % 6);
                            const uint8_t* src = jj == 2 ? reinterpret_cast<const uint8_t*>(p.flo + (size_t)UU * 32 * C)
                                : reinterpret_cast<const uint8_t*>(p.fhi + (size_t)(bb + (jj > 2 ? 24 : 0)) * 16 * C) + ((jj == 1 || jj == 4) ? GB : 0);
                            if (!prev) mbar_wait(sb + B_FULL + 8 * (NG - PACE), 0);
                            if (mbar_test(sb + B_Q, 0)) break;
                            l2_prefetch(src, GB);
                            if (prev) { if (ld_rlx(reinterpret_cast<const uint32_t*>(prev + GB - 4)) == 0x9e3779b9u) __nanosleep(1); }
                            else mbar_wait(sb + B_FULL + 8 * (NG - 1), 0);
                            prev = src;
                        }
                    }
                    const uint32_t dst = sb + SM_RING + slot * GB, bar = sb + B_FULL + 8 * slot;
                    mbar_wait(sb + B_EMPTY + 8 * slot, ph);
                    if (cnt >= NG && k >= WINK) {
                        const int c = cnt - (k >= WINK2 ? WIN2 : WIN);
                        mbar_wait(sb + B_FULL + 8 * (c % NG), (c / NG) & 1);
                    }
                    cnt++;
                    if (j == CLAIM_J) Un = (STATIC || k < NSTAT - 1) ? U + NCTA : NSTAT * NCTA + (int)atomicAdd(&g_next, 1u);
                    mbar_expect(bar, GB);
                    if (j == 2) tma3(dst, &tmLo, 32 * U, 0, bar, pol);
                    else tma5(dst, &tmHi, b0 + (j > 2 ? 24 : 0), (j == 1 || j == 4) ? 3 : 0, bar, pol);
                    if (++slot == NG) { slot = 0; ph ^= 1; }
                }
                if (k == PFK) {
                    l2_prefetch(reinterpret_cast<const uint8_t*>(p.w1) + cta * 9216, 9216);
                    l2_prefetch(reinterpret_cast<const uint8_t*>(p.w2) + cta * 9216, 9216);
                }
                U = Un;
                asm volatile("st.volatile.shared.u32 [%0], %1;" ::"r"(sb + S_MORE + 4 * (k & 3)), "r"(2 * (k + 1) + (U < NU)) : "memory");
            }
            poll_ge(&g_cntW[32], *stag * 288u);
            fence_async();
            for (int j = 0; j < (cta < 96 ? 6 : 2); j++) {
                const uint32_t bytes = j == 1 ? GB / 2 : GB, bar = sb + B_FULL + 8 * slot;
                const uint32_t dst = sb + SM_RING + slot * GB;
                mbar_wait(sb + B_EMPTY + 8 * slot, ph);
                mbar_expect(bar, bytes);
                if (j < 2) bulk_g2s(dst, &g_WcF[(cta & 15) * 2304 + j * 1536], bytes, bar);
                else if (j < 4) tma2(dst, &tmW1, 64 * (cta % 24), 192 * (j - 2), bar);
                else for (int i = 0; i < 3; i++) tma2(dst + i * 8192, &tmW2, 16 * (cta % 24), 768 * (j - 4) + 256 * i, bar);
                if (++slot == NG) { slot = 0; ph ^= 1; }
            }
            TS(3);
        } else if (wid >= 1) {
            const int hw = (cta - 32) * 3 + wid - 1;
            if (WCE && hw >= 0) { if (WCE > 1) __nanosleep(WCE); wcomb(p, stag, hw, lane, sb + B_Q); }
            mbar_wait(sb + B_Q, 0);
            if (!WCE && tid == 32) {
                l2_prefetch(reinterpret_cast<const uint8_t*>(p.wo) + cta * 2304, 2304);
                l2_prefetch(reinterpret_cast<const uint8_t*>(p.wkv) + cta * 4608, 4608);
            }
            {
                static_assert(X_END % (4 * NCTA) == 0, "");
                constexpr int ZN = X_END / 4 / NCTA;
                for (int i = tid - 32; i < ZN; i += 96) reinterpret_cast<uint4*>(g_x)[cta * ZN + i] = make_uint4(0, 0, 0, 0);
                if (tid - 32 < 48) g_act[(*stag & 1) ^ 1][cta * 48 + tid - 32] = make_uint4(0, 0, 0, 0);
                __syncwarp();
                if (lane == 0) { fence_gpu(); mbar_arrive(sb + B_Z); }
            }
            if (!WCE && hw >= 0) wcomb(p, stag, hw, lane, sb + B_Q);
        }
        return;
    } else if (wid < 8) {
        float s[16], s2[16], slo[16], sl2[16];
        const uint32_t lq = dlB(sb + SM_Q);
        if (cta < NPRO) {
            if (cta >= 6) {
                const uint4* src = g_act[*stag & 1] + (cta < 12 ? 0 : 1536);
                fetch_img<12, 128>(sm + SM_Q, src, tid - 128);
            }
            bar_sync(1, 128);
            if (tid == 128) TS(14);
            mbar_wait(sb + B_FULL, 0); mbar_wait(sb + B_FULL + 8, 0);
            wg_fence();
            if (cta < 6) wgchain2<1, 1024, 24, 1, 2048, 0, 0, 0, 0>(s, s2, dlA(sb + SM_RING), lq);
            else wgchain2<0, 1024, 24, 4, 8192, 32, 0, 0, 0>(s, s2, dlA(sb + SM_RING), lq);
            wg_commit(); wg_wait0(); pin(s); pin(s2);
#pragma unroll
            for (int i = 0; i < 16; i++) s[i] += s2[i];
            if (lane < 2) { mbar_arrive(sb + B_EMPTY); mbar_arrive(sb + B_EMPTY + 8); }
            const float sc = cta < 12 ? 1.0f : 0.05103103630798288f * 1.4426950408889634f;
            uint32_t* dst = reinterpret_cast<uint32_t*>(const_cast<uint4*>(g_act[*stag & 1])) + cta * 1024 + w * 256 + lane;
#pragma unroll
            for (int n = 0; n < 4; n++) {
                st_rlx(dst + 32 * n, ~movtrans(pack2(s[4 * n] * sc, s[4 * n + 1] * sc)));
                st_rlx(dst + 128 + 32 * n, ~movtrans(pack2(s[4 * n + 2] * sc, s[4 * n + 3] * sc)));
            }
            if (cta >= 12) { bar_sync(1, 128); if (tid == 128) st_rlx(&g_flagP[cta], *stag); }
            if (tid == 128) TS(1);
        }
        if (w == 0) gate_img(12, 12, lane, ld_rlx(&g_flagP[lane]), *stag);
        bar_sync(2, 384);
        fetch_img<8, 384>(sm + SM_Q, g_act[*stag & 1] + 2 * 1536, tid - 128);
        mbar_arrive(sb + B_Q);
        mbar_wait(sb + B_Q, 0);
        if (tid == 128) TS(2);
        float mth[8], lsum[8], pd[8], mlane = -INFINITY;
#pragma unroll
        for (int i = 0; i < 8; i++) { mth[i] = -INFINITY; lsum[i] = 0.f; pd[i] = 0.f; }
        float* wmax = reinterpret_cast<float*>(sm + SM_WMAX);
        float* alpha = reinterpret_cast<float*>(sm + SM_ALPHA);
        const int col = 8 * (lane >> 3) + 2 * t + (g & 1);
        for (int k = 0, go = 1; go; go = more_units(sb, k), k++) {
#pragma unroll
            for (int tb = 0; tb < 2; tb++) {
#pragma unroll
                for (int h = 0; h < 2; h++) {
                    const uint32_t ga = dlA(sb + SM_RING + slot * GB);
                    mbar_wait(sb + B_FULL + 8 * slot, ph);
                    if (++slot == NG) { slot = 0; ph ^= 1; }
                    wg_fence();
                    if (h == 0) wgchain2<0, 1024, 12, 4, 8192, 32, 0, 0, 0>(s, s2, ga, lq);
                    else wgchain2<0, 1024, 12, 4, 8192, 32, 0, 12288, 1>(s, s2, ga, lq);
                }
                if (tb == 0) {
                    const uint32_t gl = dlA(sb + SM_RING + slot * GB);
                    mbar_wait(sb + B_FULL + 8 * slot, ph);
                    if (++slot == NG) { slot = 0; ph ^= 1; }
                    wg_fence();
                    wgchain2<0, 512, 24, 4, 4096, 32, 0, GB, 0>(slo, sl2, gl, lq);
                }
                wg_commit(); wg_wait0(); pin(s); pin(s2);
                if (tb == 0) {
                    pin(slo); pin(sl2);
#pragma unroll
                    for (int i = 0; i < 16; i++) slo[i] += sl2[i];
                }
                float mx[8];
#pragma unroll
                for (int n = 0; n < 4; n++)
#pragma unroll
                    for (int i = 0; i < 2; i++) {
                        s[4 * n + i] += s2[4 * n + i] + slo[4 * n + i]; s[4 * n + 2 + i] += s2[4 * n + 2 + i] + slo[4 * n + i];
                        mx[2 * n + i] = fmaxf(s[4 * n + i], s[4 * n + 2 + i]);
                    }
                const bool b4 = lane & 16, b3 = lane & 8, b2 = lane & 4;
#pragma unroll
                for (int j = 0; j < 4; j++) mx[j] = fmaxf(b4 ? mx[4 + j] : mx[j], __shfl_xor_sync(~0u, b4 ? mx[j] : mx[4 + j], 16));
#pragma unroll
                for (int j = 0; j < 2; j++) mx[j] = fmaxf(b3 ? mx[2 + j] : mx[j], __shfl_xor_sync(~0u, b3 ? mx[j] : mx[2 + j], 8));
                const float cm = fmaxf(b2 ? mx[1] : mx[0], __shfl_xor_sync(~0u, b2 ? mx[0] : mx[1], 4));
                bar_sync(1, 128);
                wmax[w * 32 + col] = cm;
                bar_sync(1, 128);
                const float mnew = fmaxf(fmaxf(mlane, fmaxf(wmax[col], wmax[32 + col])), fmaxf(wmax[64 + col], wmax[96 + col]));
                mbar_wait(sb + B_PEMPTY + 8 * tb, (k & 1) ^ 1);
                if (w == 0) alpha[tb * 32 + col] = ex2(mlane - mnew);
                mlane = mnew;
                uint32_t pk[8];
#pragma unroll
                for (int n = 0; n < 4; n++) {
#pragma unroll
                    for (int i = 0; i < 2; i++) {
                        const int j = 2 * n + i;
                        const float mn = __shfl_sync(~0u, mnew, t + 4 * i + 8 * n);
                        const float a = ex2(mth[j] - mn);
                        mth[j] = mn;
                        const float p0 = ex2(s[4 * n + i] - mn), p1 = ex2(s[4 * n + 2 + i] - mn);
                        s[4 * n + i] = p0; s[4 * n + 2 + i] = p1;
                        lsum[j] = lsum[j] * a + (p0 + p1);
                        pd[j] = tb == 0 ? p0 + p1 : pd[j] * a + (p0 + p1);
                    }
                    pk[2 * n] = pack2(s[4 * n], s[4 * n + 1]); pk[2 * n + 1] = pack2(s[4 * n + 2], s[4 * n + 3]);
                }
                const uint32_t pa = sb + SM_P + tb * 4096 + (2 * w + ((lane >> 3) & 1)) * 512 + (8 * (lane >> 4) + (lane & 7)) * 16;
                stsm4t(pa, pk[0], pk[1], pk[2], pk[3]);
                stsm4t(pa + 256, pk[4], pk[5], pk[6], pk[7]);
                if (tb == 1) stsm4t(sb + SM_PD + w * 512 + lane * 16, pack2(pd[0], pd[1]), pack2(pd[2], pd[3]), pack2(pd[4], pd[5]), pack2(pd[6], pd[7]));
                fence_async_s();
                mbar_arrive(sb + B_PFULL + 8 * tb);
            }
        }
        {
            const bool b4 = lane & 16, b3 = lane & 8, b2 = lane & 4;
#pragma unroll
            for (int j = 0; j < 4; j++) lsum[j] = (b4 ? lsum[4 + j] : lsum[j]) + __shfl_xor_sync(~0u, b4 ? lsum[j] : lsum[4 + j], 16);
#pragma unroll
            for (int j = 0; j < 2; j++) lsum[j] = (b3 ? lsum[2 + j] : lsum[j]) + __shfl_xor_sync(~0u, b3 ? lsum[j] : lsum[2 + j], 8);
            const float cl = (b2 ? lsum[1] : lsum[0]) + __shfl_xor_sync(~0u, b2 ? lsum[0] : lsum[1], 4);
            bar_sync(1, 128);
            wmax[w * 32 + col] = cl;
            bar_sync(1, 128);
            float* ml = reinterpret_cast<float*>(sm + SM_Q);
            if (w == 0) { ml[col] = mlane; ml[32 + col] = (wmax[col] + wmax[32 + col]) + (wmax[64 + col] + wmax[96 + col]); }
            bar_sync(1, 128);
            const uint32_t par = *stag & 1;
            const uint4 mv = reinterpret_cast<const uint4*>(ml)[(tid - 128) >> 4], lv = reinterpret_cast<const uint4*>(ml)[8 + ((tid - 128) >> 4)];
            uint4* o = &g_U[(cta * 128 + tid - 128) * 26 + 24];
            o[0] = make_uint4((mv.x & ~1u) | par, (mv.y & ~1u) | par, (mv.z & ~1u) | par, (mv.w & ~1u) | par);
            o[1] = make_uint4((lv.x & ~1u) | par, (lv.y & ~1u) | par, (lv.z & ~1u) | par, (lv.w & ~1u) | par);
            asm volatile("bar.arrive 3, 384;" ::: "memory");
        }
    } else {
        const int hf = (wid >> 2) - 2;
        bar_sync(2, 384);
        fetch_img<8, 384>(sm + SM_Q, g_act[*stag & 1] + 2 * 1536, tid - 128);
        mbar_arrive(sb + B_Q);
        float acc[6][16];
#pragma unroll
        for (int b = 0; b < 6; b++)
#pragma unroll
            for (int i = 0; i < 16; i++) acc[b][i] = 0.f;
        const float2* alpha = reinterpret_cast<const float2*>(sm + SM_ALPHA);
        const uint32_t lp = dlB(sb + SM_P);
        for (int k = 0, go = 1; go; go = more_units(sb, k), k++) {
            int sl = 0;
#pragma unroll
            for (int tb = 0; tb < 2; tb++) {
                const int s0 = slot; if (++slot == NG) { slot = 0; ph ^= 1; }
                const int s1 = slot; if (++slot == NG) { slot = 0; ph ^= 1; }
                if (tb == 0) { sl = slot; if (++slot == NG) { slot = 0; ph ^= 1; } }
                const uint32_t gh = dlA(sb + SM_RING + (hf ? s1 : s0) * GB), gl = dlA(sb + SM_RING + sl * GB + hf * 12288), lb = lp + tb * 256;
                mbar_wait(sb + B_PFULL + 8 * tb, k & 1);
#pragma unroll
                for (int n = 0; n < 4; n++) {
                    const float2 a = alpha[tb * 16 + 4 * n + t];
#pragma unroll
                    for (int b = 0; b < 6; b++) { acc[b][4 * n] *= a.x; acc[b][4 * n + 1] *= a.y; acc[b][4 * n + 2] *= a.x; acc[b][4 * n + 3] *= a.y; }
                }
                wg_fence();
                if (tb == 1) wgpv<2, 4096, 8192>(acc[3], acc[4], acc[5], gl, lp);
                wgpv<4, 8192, 0>(acc[0], acc[1], acc[2], gh, lb);
                wg_commit(); wg_wait0();
#pragma unroll
                for (int b = 0; b < 6; b++) pin(acc[b]);
                if (lane == 0) {
                    if (tb == 1) mbar_arrive(sb + B_EMPTY + 8 * sl);
                    mbar_arrive(sb + B_EMPTY + 8 * s0); mbar_arrive(sb + B_EMPTY + 8 * s1);
                    mbar_arrive(sb + B_PEMPTY + 8 * tb);
                }
            }
        }
        if (tid == 256) TS(4);
        uint2* ub = reinterpret_cast<uint2*>(g_U) + (size_t)cta * 128 * 52 + (t >> 1) * 16 * 52 + g * 2 + (t & 1);
        const uint32_t par = *stag & 1;
#pragma unroll
        for (int b = 0; b < 6; b++) {
            const int si = 4 * ((b < 3 ? b : b + 3) + 3 * hf) + w, cs = si / 3, sub = si - 3 * cs;
#pragma unroll
            for (int n = 0; n < 4; n++) {
                const float x0 = __uint_as_float((__float_as_uint(acc[b][4 * n]) + 0x10000u) & 0xfffe0000u);
                ub[(2 * n * 16 + cs) * 52 + sub * 16] = make_uint2(pack2(x0, acc[b][4 * n + 1]) | par, pack2(acc[b][4 * n + 2], acc[b][4 * n + 3]));
            }
        }
        bar_sync(3, 384);
        if (tid == 256) { mbar_wait(sb + B_Z, 0); st_rlx(&g_done[cta], *stag); TS(5); }
    }
    tail(p, *stag, sm, sb, slot, ph);
}

typedef CUresult (*EncFn)(CUtensorMap*, CUtensorMapDataType, cuuint32_t, void*, const cuuint64_t*, const cuuint64_t*, const cuuint32_t*,
                          const cuuint32_t*, CUtensorMapInterleave, CUtensorMapSwizzle, CUtensorMapL2promotion, CUtensorMapFloatOOBfill);
void enc(EncFn fn, CUtensorMap* m, const void* base, int rank, const cuuint64_t* dims, const cuuint64_t* str, const cuuint32_t* box,
         CUtensorMapSwizzle sw = CU_TENSOR_MAP_SWIZZLE_128B) {
    const cuuint32_t es[5] = {1, 1, 1, 1, 1};
    fn(m, CU_TENSOR_MAP_DATA_TYPE_BFLOAT16, rank, const_cast<void*>(base), dims, str, box, es, CU_TENSOR_MAP_INTERLEAVE_NONE,
       sw, CU_TENSOR_MAP_L2_PROMOTION_L2_256B, CU_TENSOR_MAP_FLOAT_OOB_FILL_NONE);
}
}

extern "C" void kernel_launch(void* const* d_in, const int* in_sizes, int n_in, void* d_out, int out_size) {
    static EncFn fn = nullptr;
    if (!fn) {
        cudaDriverEntryPointQueryResult qr;
        cudaGetDriverEntryPoint("cuTensorMapEncodeTiled", reinterpret_cast<void**>(&fn), cudaEnableDefault, &qr);
        cudaFuncSetAttribute(detr_kernel, cudaFuncAttributeMaxDynamicSharedMemorySize, SM_TOTAL);
    }
    Params p;
    p.q = (const bf16*)d_in[0]; p.fhi = (const bf16*)d_in[1]; p.flo = (const bf16*)d_in[2];
    p.lat_hi = (const bf16*)d_in[3]; p.lat_lo = (const bf16*)d_in[4];
    p.wkv = (const bf16*)d_in[6]; p.wo = (const bf16*)d_in[7]; p.w1 = (const bf16*)d_in[8]; p.w2 = (const bf16*)d_in[9];
    p.out = (bf16*)d_out;
    CUtensorMap mHi, mLo, mWq, mWk, mLh, mLl, mW1, mW2;
    { const cuuint64_t d[5] = {64, 8, 2, 9216, 6}, s[4] = {1536, 768, 12288, 128}; const cuuint32_t b[5] = {64, 8, 2, 4, 3}; enc(fn, &mHi, p.fhi, 5, d, s, b); }
    { const cuuint64_t d[3] = {64, 36864, 6}, s[2] = {768, 128}; const cuuint32_t b[3] = {64, 32, 6}; enc(fn, &mLo, p.flo, 3, d, s, b); }
    { const cuuint64_t d[2] = {384, 384}, s[1] = {768}; const cuuint32_t b[2] = {64, 192}; enc(fn, &mWq, d_in[5], 2, d, s, b); }
    { const cuuint64_t d[3] = {64, 384, 6}, s[2] = {1536, 128}; const cuuint32_t b[3] = {64, 64, 3}; enc(fn, &mWk, p.wkv, 3, d, s, b); }
    { const cuuint64_t d[3] = {64, 384, 6}, s[2] = {768, 128}; const cuuint32_t b[3] = {64, 64, 3};
      enc(fn, &mLh, p.lat_hi, 3, d, s, b); enc(fn, &mLl, p.lat_lo, 3, d, s, b); }
    { const cuuint64_t d[2] = {1536, 384}, s[1] = {3072}; const cuuint32_t b[2] = {64, 192}; enc(fn, &mW1, p.w1, 2, d, s, b); }
    { const cuuint64_t d[2] = {384, 1536}, s[1] = {768}; const cuuint32_t b[2] = {16, 256}; enc(fn, &mW2, p.w2, 2, d, s, b, CU_TENSOR_MAP_SWIZZLE_NONE); }
    detr_kernel<<<NCTA, 512, SM_TOTAL, cudaStreamPerThread>>>(mHi, mLo, mWq, mWk, mLh, mLl, mW1, mW2, p);
}
```
